```python
import torch

def _softmax(x, axis=-1):
    return torch.softmax(x, dim=axis)
def _gelu(x):
    return torch.nn.functional.gelu(x, approximate="tanh")
def _silu(x):
    return torch.nn.functional.silu(x)
def _sigmoid(x):
    return torch.sigmoid(x)
def _layernorm(x, axis=-1, eps=1e-5):
    m = x.mean(dim=axis, keepdim=True)
    v = x.var(dim=axis, keepdim=True, unbiased=False)
    return (x - m) / torch.sqrt(v + eps)
def _scatter_add(tgt, idx, src, axis=0):
    return tgt.clone().index_add_(axis, idx, src)
def _segment_sum(src, seg, n):
    out = torch.zeros((n,) + src.shape[1:], dtype=src.dtype)
    return out.index_add_(0, seg, src)
def _pad(x, pw):
    flat = tuple(v for pair in reversed(pw) for v in pair)
    return torch.nn.functional.pad(x, flat)

kernel_name = 'standalone__weight_only_int_gptq__prompt'

def setup_inputs():

    _w = (lambda a: (lambda t: t.to(torch.bfloat16) if t.is_floating_point() else t)(torch.as_tensor(a)))
    B, S, D, F = 1, 2048, 576, 4608
    bits = max(2, min(4, 3))
    pf = 32 // bits
    G = -1 if -1 > 0 else D
    G = max(pf, (G // pf) * pf)
    D = max(G, (D // G) * G)
    ng = D // G
    qmax = 1 << bits
    qw = torch.randint(0, qmax, (D, F)).to(torch.int64)
    packed = torch.zeros((D // pf, F), dtype=torch.int64)
    for i in range(pf):
        packed |= (qw[i::pf] << (i * bits))
    packed = packed.to(torch.int32)
    return {
        "x": _w((lambda *s: torch.randn(*s, dtype=torch.bfloat16) * 0.05)(B, S, D)),
        "qw_packed": _w(packed),
        "scales": _w(torch.abs((lambda *s: torch.randn(*s, dtype=torch.bfloat16) * 0.05)(ng, F)).to(float) * 0.1 + 0.01),
        "zeros": _w(torch.randint(0, qmax, (ng, F)).to(float)),
        "bits": _w((lambda _x: torch.as_tensor(_x, dtype=torch.int32))(bits)),
    }

def reference(x, qw_packed, scales, zeros, bits):
    b = int(bits)
    pf = 32 // b
    mask = (1 << b) - 1
    P, F = qw_packed.shape
    D = P * pf
    ng = scales.shape[0]
    G = D // ng
    shifts = (lambda x, dt: x.to(dt))(torch.arange(pf) * b, qw_packed.dtype)
    qw = ((qw_packed[:, None, :] >> shifts[None, :, None]) & mask).reshape(D, F)
    s = (lambda x, n, axis: torch.repeat_interleave(x, n, dim=axis))(scales, G, axis=0)
    z = (lambda x, n, axis: torch.repeat_interleave(x, n, dim=axis))(zeros, G, axis=0)
    w = ((lambda x, dt: x.to(dt))(qw, x.dtype) - z) * s
    return torch.einsum("bsd,df->bsf", x, w)
```

```cpp
#include <cuda_runtime.h>
#include <cuda_bf16.h>
#include <cuda.h>
#include <stdint.h>
#include <type_traits>

#define DEV __device__ __forceinline__

#define PAUSE_AT 6
#define PAUSE_UNTIL 8
#define EPI_HMUL 1
#define PREF 1
#define WFIRST 0
#define WINDOW 3
#define T3FENCE 1
#define CWAIT mbar_spin
#define T0MODE 2
#define THROTTLE 0
#define ALLFENCE 0
#define S0 20
#define DQB_SHF 0
#define BURSTFENCE 1
#define T3_UNTIL 8
#define WWAIT mbar_spin
#define XWAIT mbar_spin
#define DIRECT 1
#define SPLIT 2
#define PACE 0
#define PACE2 450
#define PROLOG 1
#define STHINT 0
#define GATE 1
#define LAYA 1

namespace {

constexpr int      kF        = 4608;
constexpr int      kXJ       = 568;
constexpr uint32_t kStage    = 16384;
constexpr int      kTailN    = 104;
constexpr int      kTailBox  = 56;
constexpr uint32_t kTailBlk  = kTailN * 128;
constexpr uint32_t XT        = 0;
constexpr uint32_t XS        = 17 * 1024;
constexpr uint32_t OS        = XS + 9 * kStage;
constexpr uint32_t WS        = OS + 2 * kStage;
constexpr uint32_t kPiece    = 8 * 512;
constexpr uint32_t ZS        = WS + 8 * kPiece;
constexpr uint32_t BARS      = ZS + 768;
constexpr uint32_t FULL      = BARS;
constexpr uint32_t TFULL     = BARS + 72;
constexpr uint32_t EMPTY     = BARS + 144;
constexpr uint32_t WFULL     = BARS + 216;
constexpr uint32_t DONE      = BARS + 224;
constexpr uint32_t kSmem     = BARS + 240;
__host__ __device__ constexpr int tail_stage(int i) { return ((i + 1) * (int)kTailBlk - (int)XS - 1) / (int)kStage; }

#define TL(slot, idx) do {} while (0)
#define TG(slot, idx) do {} while (0)
#define TDUMP(slot) do {} while (0)
#define TL1(slot, idx) do {} while (0)
#define TG1(slot, idx) do {} while (0)
#define TDUMP1(slot) do {} while (0)
constexpr uint32_t kSmemTot = kSmem;

#define TLB(slot, idx) do {} while (0)
#define TLB1(slot, idx) do {} while (0)
DEV void mbar_init(uint32_t a, uint32_t c) { asm volatile("mbarrier.init.shared::cta.b64 [%0], %1;" :: "r"(a), "r"(c) : "memory"); }
DEV void mbar_expect(uint32_t a, uint32_t tx) { asm volatile("mbarrier.arrive.expect_tx.shared::cta.b64 _, [%0], %1;" :: "r"(a), "r"(tx) : "memory"); }
DEV void mbar_wait(uint32_t a, uint32_t par) {
    asm volatile("{\n.reg .pred p;\nL:\nmbarrier.try_wait.parity.shared::cta.b64 p, [%0], %1;\n@!p bra.uni L;\n}"
                 :: "r"(a), "r"(par) : "memory");
}
DEV void mbar_spin(uint32_t a, uint32_t par) {
    asm volatile("{\n.reg .pred p;\nL:\nmbarrier.test_wait.parity.shared::cta.b64 p, [%0], %1;\n@!p bra.uni L;\n}"
                 :: "r"(a), "r"(par) : "memory");
}
DEV void mbar_tt(uint32_t a, uint32_t par) {
    asm volatile("{\n.reg .pred p;\nmbarrier.test_wait.parity.shared::cta.b64 p, [%0], %1;\n@p bra.uni D;\n"
                 "L:\nmbarrier.try_wait.parity.shared::cta.b64 p, [%0], %1;\n@!p bra.uni L;\nD:\n}"
                 :: "r"(a), "r"(par) : "memory");
}
DEV bool mbar_try(uint32_t a, uint32_t par) {
    uint32_t ok;
    asm volatile("{\n.reg .pred p;\nmbarrier.try_wait.parity.shared::cta.b64 p, [%1], %2;\nselp.u32 %0, 1, 0, p;\n}"
                 : "=r"(ok) : "r"(a), "r"(par) : "memory");
    return ok;
}
DEV void arrive_cluster_if(uint32_t a, bool p) {
    asm volatile("{\n.reg .pred p;\nsetp.ne.b32 p, %1, 0;\n@p mbarrier.arrive.shared::cluster.b64 _, [%0];\n}"
                 :: "r"(a), "r"((uint32_t)p) : "memory");
}
DEV void tma_ld(uint32_t dst, const CUtensorMap* m, int c0, int c1, uint32_t bar) {
    asm volatile("cp.async.bulk.tensor.2d.shared::cluster.global.mbarrier::complete_tx::bytes [%0], [%1, {%3, %4}], [%2];"
                 :: "r"(dst), "l"(m), "r"(bar), "r"(c0), "r"(c1) : "memory");
}
DEV void tma_ld3(uint32_t dst, const CUtensorMap* m, int c1, int c2, uint32_t bar) {
    asm volatile("cp.async.bulk.tensor.3d.shared::cluster.global.mbarrier::complete_tx::bytes [%0], [%1, {0, %3, %4}], [%2];"
                 :: "r"(dst), "l"(m), "r"(bar), "r"(c1), "r"(c2) : "memory");
}
DEV void w_piece(uint32_t dst, const CUtensorMap* m, int f, int row, uint32_t bar) {
    if (LAYA) tma_ld3(dst, m, row, f >> 4, bar); else tma_ld(dst, m, f, row, bar);
}
DEV void tma_ld_mc(uint32_t dst, const CUtensorMap* m, int c0, int c1, uint32_t bar) {
    asm volatile("cp.async.bulk.tensor.2d.shared::cluster.global.mbarrier::complete_tx::bytes.multicast::cluster [%0], [%1, {%3, %4}], [%2], %5;"
                 :: "r"(dst), "l"(m), "r"(bar), "r"(c0), "r"(c1), "h"((uint16_t)3) : "memory");
}
DEV void bulk_ld(uint32_t dst, const void* src, uint32_t bytes, uint32_t bar) {
    asm volatile("cp.async.bulk.shared::cluster.global.mbarrier::complete_tx::bytes [%0], [%1], %2, [%3];"
                 :: "r"(dst), "l"(src), "r"(bytes), "r"(bar) : "memory");
}
DEV uint32_t lds32(uint32_t a) { uint32_t v; asm volatile("ld.shared.b32 %0, [%1];" : "=r"(v) : "r"(a)); return v; }
DEV void tma_st(const CUtensorMap* m, int c0, int c1, uint32_t src) {
    asm volatile("cp.async.bulk.tensor.2d.global.shared::cta.bulk_group [%0, {%2, %3}], [%1];"
                 :: "l"(m), "r"(src), "r"(c0), "r"(c1) : "memory");
    asm volatile("cp.async.bulk.commit_group;" ::: "memory");
}
DEV void tma_st_wait_read() { asm volatile("cp.async.bulk.wait_group.read 0;" ::: "memory"); }
DEV bool elect_one() {
    uint32_t p;
    asm volatile("{\n.reg .pred p;\nelect.sync _|p, 0xffffffff;\nselp.u32 %0, 1, 0, p;\n}" : "=r"(p));
    return p;
}
DEV uint32_t ldg_early(const uint32_t* p) { uint32_t v; asm volatile("ld.global.nc.b32 %0, [%1];" : "=r"(v) : "l"(p)); return v; }
DEV int fresh_lane() { int v; asm volatile("mov.u32 %0, %%laneid;" : "=r"(v)); return v; }
DEV void sched_fence() { uint32_t c; asm volatile("mov.u32 %0, %%clock;" : "=r"(c) :: "memory"); }
DEV void pf_l2(const void* p) { asm volatile("prefetch.global.L2 [%0];" :: "l"(p)); }
DEV void prefetch_map(const CUtensorMap* m) { asm volatile("prefetch.tensormap [%0];" :: "l"(m) : "memory"); }
DEV void cluster_arrive() { asm volatile("barrier.cluster.arrive.relaxed.aligned;" ::: "memory"); }
DEV void cluster_wait() { asm volatile("barrier.cluster.wait.aligned;" ::: "memory"); }
DEV void cluster_arrive1() { asm volatile("barrier.cluster.arrive.relaxed;" ::: "memory"); }
DEV void cluster_wait1() { asm volatile("barrier.cluster.wait;" ::: "memory"); }
DEV void bar_sync(int id) { asm volatile("bar.sync %0, 128;" :: "r"(id) : "memory"); }
DEV void wg_fence() { asm volatile("wgmma.fence.sync.aligned;" ::: "memory"); }
DEV void wg_commit() { asm volatile("wgmma.commit_group.sync.aligned;" ::: "memory"); }
template <int N> DEV void wg_wait() { asm volatile("wgmma.wait_group.sync.aligned %0;" :: "n"(N) : "memory"); }

#define ACC8(d, o) "+f"(d[o + 0]), "+f"(d[o + 1]), "+f"(d[o + 2]), "+f"(d[o + 3]), "+f"(d[o + 4]), "+f"(d[o + 5]), "+f"(d[o + 6]), "+f"(d[o + 7])

template <int ACCUM>
DEV void wgmma_n128(float (&d)[64], uint32_t a0, uint32_t a1, uint32_t a2, uint32_t a3, uint64_t desc) {
    asm volatile(
        "wgmma.mma_async.sync.aligned.m64n128k16.f32.bf16.bf16 "
        "{%0,%1,%2,%3,%4,%5,%6,%7,%8,%9,%10,%11,%12,%13,%14,%15,%16,%17,%18,%19,%20,%21,%22,%23,%24,%25,%26,%27,%28,%29,%30,%31,"
        "%32,%33,%34,%35,%36,%37,%38,%39,%40,%41,%42,%43,%44,%45,%46,%47,%48,%49,%50,%51,%52,%53,%54,%55,%56,%57,%58,%59,%60,%61,%62,%63},"
        "{%64,%65,%66,%67}, %68, %69, 1, 1, 0;\n"
        : ACC8(d, 0), ACC8(d, 8), ACC8(d, 16), ACC8(d, 24), ACC8(d, 32), ACC8(d, 40), ACC8(d, 48), ACC8(d, 56)
        : "r"(a0), "r"(a1), "r"(a2), "r"(a3), "l"(desc), "n"(ACCUM));
}
template <int ACCUM>
DEV void wgmma_n104(float (&d)[64], uint32_t a0, uint32_t a1, uint32_t a2, uint32_t a3, uint64_t desc) {
    asm volatile(
        "wgmma.mma_async.sync.aligned.m64n104k16.f32.bf16.bf16 "
        "{%0,%1,%2,%3,%4,%5,%6,%7,%8,%9,%10,%11,%12,%13,%14,%15,%16,%17,%18,%19,%20,%21,%22,%23,%24,%25,%26,%27,%28,%29,%30,%31,"
        "%32,%33,%34,%35,%36,%37,%38,%39,%40,%41,%42,%43,%44,%45,%46,%47,%48,%49,%50,%51},"
        "{%52,%53,%54,%55}, %56, %57, 1, 1, 0;\n"
        : ACC8(d, 0), ACC8(d, 8), ACC8(d, 16), ACC8(d, 24), ACC8(d, 32), ACC8(d, 40),
          "+f"(d[48]), "+f"(d[49]), "+f"(d[50]), "+f"(d[51])
        : "r"(a0), "r"(a1), "r"(a2), "r"(a3), "l"(desc), "n"(ACCUM));
}

struct DqState {
    uint32_t addr[5];
    uint32_t addr0;
    uint32_t mul[5];
    uint32_t z0, z1;
    uint32_t magic;
    int j;
};

constexpr uint32_t kMagic = 0x41004280u;
template <int LAY, bool SHF>
DEV void dq_setup(DqState& q, uint32_t slab, int j, int g, int t) {
    const int e = t - j;
#pragma unroll
    for (int r = 0; r < 5; r++) {
        const int n = 4 * r + e + 5;
        const int w = (n * 52) >> 8;
        const int sub = n - 5 * w;
        q.addr[r] = slab + (w - 1) * (LAY == 0 ? 512 : 64) + g * 8;
        if (SHF) q.mul[r] = 25 - 6 * sub;
        else asm("shl.b32 %0, 1, %1;" : "=r"(q.mul[r]) : "r"(25 - 6 * sub));
    }
    q.addr0 = q.addr[0] - (e < 0 ? 4096 - 512 : 0);
    q.j = j;
    q.magic = kMagic;
}

DEV uint32_t bf2_add(uint32_t a, uint32_t b) { uint32_t d; asm("add.rn.bf16x2 %0, %1, %2;" : "=r"(d) : "r"(a), "r"(b)); return d; }
DEV uint32_t bf2_sub(uint32_t a, uint32_t b) { uint32_t d; asm("sub.rn.bf16x2 %0, %1, %2;" : "=r"(d) : "r"(a), "r"(b)); return d; }

template <bool FAST>
DEV void dq_zero(DqState& q, uint32_t zpair) {
    const uint32_t z0 = __byte_perm(zpair, 0, 0x1010), z1 = __byte_perm(zpair, 0, 0x3232);
    q.z0 = FAST ? bf2_add(z0, kMagic) : z0;
    q.z1 = FAST ? bf2_add(z1, kMagic) : z1;
}

template <bool FAST, bool SHF>
DEV uint32_t dq_pair(uint32_t w, uint32_t mul, uint32_t z, uint32_t magic) {
    uint32_t y;
    if (SHF) y = w << mul;
    else asm("mul.lo.u32 %0, %1, %2;" : "=r"(y) : "r"(w), "r"(mul));
    y = __byte_perm(y, 0, 0x3333);
    asm("lop3.b32 %0, %1, 0x0070000E, %2, 0xEA;" : "=r"(y) : "r"(y), "r"(magic));
    if (!FAST) y = bf2_sub(y, magic);
    return bf2_sub(y, z);
}

template <int LAY, int KB>
DEV void dq_load(uint32_t (&a)[144], const DqState& q) {
#pragma unroll
    for (int u = 8 * KB; u < 8 * KB + 8; u++) {
        const int v = u / 5, r = u % 5;
        const uint32_t addr = LAY == 0 ? q.addr[r] + 2048 * v
                            : LAY == 2 ? q.addr[r] + 256 * v
                            : ((r == 0 && !(v & 1) && v > 0) ? q.addr0 : q.addr[r]) + 4096 * (v >> 1) + 256 * (v & 1);
        asm volatile("ld.shared.v2.b32 {%0, %1}, [%2];" : "=r"(a[2 * u]), "=r"(a[2 * u + 1]) : "r"(addr));
    }
}
template <bool FAST, bool SHF, int SA, int SB>
DEV void dq_conv(uint32_t (&a)[144], const DqState& q) {
#pragma unroll
    for (int u = 2 * SA; u < 2 * SB; u++) {
        const int r = u % 5;
        uint32_t x0 = dq_pair<FAST, SHF>(a[2 * u], q.mul[r], q.z0, q.magic);
        uint32_t x1 = dq_pair<FAST, SHF>(a[2 * u + 1], q.mul[r], q.z1, q.magic);
        if (u == 0 || u == 71) {
            const int t = fresh_lane() & 3;
            const bool ok = (u == 0) ? (t >= q.j) : (t <= q.j);
            x0 = ok ? x0 : 0u;
            x1 = ok ? x1 : 0u;
        }
        a[2 * u] = x0;
        a[2 * u + 1] = x1;
    }
}
template <bool FAST, int LAY, bool SHF, int KB>
DEV void dq_block(uint32_t (&a)[144], const DqState& q) { dq_load<LAY, KB>(a, q); dq_conv<FAST, SHF, 4 * KB, 4 * KB + 4>(a, q); }

template <int KB, bool TAIL, bool FENCE>
DEV void mma_block(float (&d)[64], const uint32_t (&a)[144], uint64_t dbase) {
    constexpr uint32_t off = TAIL ? XT + KB * kTailBlk : XS + KB * kStage;
    if (FENCE) wg_fence();
#pragma unroll
    for (int kk = 0; kk < 4; kk++) {
        const int s = 16 * KB + 4 * kk;
        const uint64_t desc = dbase + (off >> 4) + 2 * kk;
        if (KB == 0 && kk == 0) {
            if (TAIL) wgmma_n104<0>(d, a[s], a[s + 1], a[s + 2], a[s + 3], desc);
            else      wgmma_n128<0>(d, a[s], a[s + 1], a[s + 2], a[s + 3], desc);
        } else {
            if (TAIL) wgmma_n104<1>(d, a[s], a[s + 1], a[s + 2], a[s + 3], desc);
            else      wgmma_n128<1>(d, a[s], a[s + 1], a[s + 2], a[s + 3], desc);
        }
    }
    wg_commit();
}

template <int NC>
DEV void stage_out(const float (&d)[64], uint32_t sbase, uint32_t ost, int w) {
    const int lane = fresh_lane(), g = lane >> 2, t = lane & 3;
    const uint32_t spair = lds32(sbase + 4 * g);
    const uint32_t o0 = ost + (2 * t) * 128 + (((2 * w + (g >> 2)) ^ (2 * t)) << 4) + 4 * (g & 3);
    const uint32_t o1 = (o0 ^ 16) + 128;
    const float s0 = __uint_as_float(spair << 16), s1 = __uint_as_float(spair & 0xFFFF0000u);
#pragma unroll
    for (int c = 0; c < NC; c++) {
        uint32_t p0, p1;
        asm("cvt.rn.bf16x2.f32 %0, %1, %2;" : "=r"(p0) : "f"(d[4 * c + 2]), "f"(d[4 * c + 0]));
        asm("cvt.rn.bf16x2.f32 %0, %1, %2;" : "=r"(p1) : "f"(d[4 * c + 3]), "f"(d[4 * c + 1]));
        asm("mul.rn.bf16x2 %0, %0, %1;" : "+r"(p0) : "r"(spair));
        asm("mul.rn.bf16x2 %0, %0, %1;" : "+r"(p1) : "r"(spair));
        asm volatile("st.shared.b32 [%0], %1;" :: "r"(o0 + 1024 * c), "r"(p0) : "memory");
        asm volatile("st.shared.b32 [%0], %1;" :: "r"(o1 + 1024 * c), "r"(p1) : "memory");
    }
}

DEV void direct_out(const float (&d)[64], uint32_t sbase, char* out, int col, int cls, int row0, int w) {
    const int lane = fresh_lane(), g = lane >> 2, t = lane & 3;
    const uint32_t spair = lds32(sbase + 4 * g);
    char* p = out + (size_t)(4 * (row0 + 2 * t) + cls) * (2 * kF) + (col + 16 * w + 2 * g) * 2;
#pragma unroll
    for (int c = 0; c < kTailN / 8; c++) {
        uint32_t p0, p1;
        asm("cvt.rn.bf16x2.f32 %0, %1, %2;" : "=r"(p0) : "f"(d[4 * c + 2]), "f"(d[4 * c + 0]));
        asm("cvt.rn.bf16x2.f32 %0, %1, %2;" : "=r"(p1) : "f"(d[4 * c + 3]), "f"(d[4 * c + 1]));
        asm("mul.rn.bf16x2 %0, %0, %1;" : "+r"(p0) : "r"(spair));
        asm("mul.rn.bf16x2 %0, %0, %1;" : "+r"(p1) : "r"(spair));
        if (c < kTailN / 8 - 1 || row0 + kTailN <= 512) {
            *(uint32_t*)(p + (size_t)c * (64 * kF)) = p0;
            *(uint32_t*)(p + (size_t)c * (64 * kF) + 8 * kF) = p1;
        }
    }
}

template <int I, int N, typename F>
DEV void static_for(F&& f) {
    if constexpr (I < N) { f(std::integral_constant<int, I>{}); static_for<I + 1, N>(f); }
}

struct Work { int ja, fa, jb, fb, rb; bool tail; };

template <bool FAST>
DEV void consumer(const uint32_t sb, const Work wk, const int wg, const int w, const int lane,
                  const CUtensorMap* om, const CUtensorMap* ot, char* outp) {
    const int g = lane >> 2, t = lane & 3;
    const uint32_t full = sb + FULL;
    uint32_t rel;
    asm("mapa.shared::cluster.u32 %0, %1, %2;" : "=r"(rel) : "r"(sb + EMPTY), "r"(w & 1));
    const bool do_rel = (lane == 0) && (w < 2);
    const bool storer = (lane == 0) && (w == 3);
    const uint32_t ost = sb + OS + wg * kStage;
    const uint64_t dbase = (uint64_t)((sb & 0x3FFFF) >> 4) | (64ull << 32) | (1ull << 62);
    const uint32_t zs = sb + ZS + 128 * wg + 32 * w;
    const int ocol = wk.ja * kF + wk.fa + wg * 64;

    uint32_t a[144];
    float d[64];

    auto publish = [&](const CUtensorMap* m, int col, int row) {
        asm volatile("fence.proxy.async.shared::cta;" ::: "memory");
        bar_sync(1 + wg);
        if (storer) tma_st(m, col, row, ost);
    };
    auto staging_free = [&]() {
        if (storer) tma_st_wait_read();
        bar_sync(3 + wg);
    };

    {
        DqState q;
        dq_setup<LAYA, false>(q, sb + WS + (wg * 4 + w) * (LAYA ? 512 : 64), wk.ja, g, t);
        const uint32_t sel = 0x3210u + (uint32_t)((size_t)outp & 1);
        TL(wg, 0);
        mbar_wait(sb + WFULL, 0);
        TL(wg, 1);
        dq_zero<FAST>(q, lds32(zs + 4 * g));
        dq_load<LAYA, 0>(a, q);
        dq_conv<FAST, false, 0, 4>(a, q);
        if constexpr (T0MODE == 0) CWAIT(sb + WFULL + 8, 0);
        static_for<0, 9>([&](auto kb_) {
            constexpr int kb = decltype(kb_)::value;
            if constexpr (T0MODE == 1 && kb < 8) {
                if constexpr (kb != 3) WWAIT(sb + WFULL + 8 * (kb < 3 ? kb + 1 : kb), 0);
                dq_load<LAYA, kb + 1>(a, q);
            }
            if constexpr (kb == PAUSE_AT) { if (wg == 1) asm volatile("bar.sync 5, 256;" ::: "memory"); }
            XWAIT(full + 8 * kb, 0);
            TLB(wg, 2 + kb);
            if constexpr (T0MODE != 1 && kb < 8) dq_load<LAYA, kb + 1>(a, q);
            mma_block<kb, false, true>(d, a, dbase + (1u << 16));
            if constexpr (GATE && kb < 8 && SPLIT > 0) dq_conv<FAST, false, 4 * kb + 4, 4 * kb + 4 + SPLIT>(a, q);
            if constexpr (kb == PAUSE_UNTIL) { if (wg == 0) asm volatile("bar.arrive 5, 256;" ::: "memory"); }
            if constexpr (T0MODE == 0 && kb < 8 && SPLIT > 0) dq_conv<FAST, false, 4 * kb + 4, 4 * kb + 4 + SPLIT>(a, q);
            if constexpr (T0MODE == 0 && kb < 8) CWAIT(sb + WFULL + 8 * (kb < 2 ? kb + 2 : kb < 7 ? kb + 1 : 7), 0);
            if constexpr (kb > 0) { wg_wait<1>(); arrive_cluster_if(rel + 8 * (kb - 1), do_rel); }
            if constexpr (kb < 8) {
                uint32_t c;
                asm volatile("mov.u32 %0, %%clock;" : "=r"(c) :: "memory");
                if (GATE == 1) q.magic = __byte_perm(kMagic, c, sel);
                if (GATE == 2) { q.z0 = __byte_perm(q.z0, c, sel); q.z1 = __byte_perm(q.z1, c, sel); }
                if (GATE == 3) { q.mul[(8 * kb + 10) % 5] = __byte_perm(q.mul[(8 * kb + 10) % 5], c, sel); q.mul[(8 * kb + 11) % 5] = __byte_perm(q.mul[(8 * kb + 11) % 5], c, sel); q.mul[(8 * kb + 12) % 5] = __byte_perm(q.mul[(8 * kb + 12) % 5], c, sel); }
            }
            if constexpr (kb < 8) dq_conv<FAST, false, 4 * kb + 4 + ((T0MODE == 0 || GATE) ? SPLIT : 0), 4 * kb + 8>(a, q);
        });
    }

    const bool tail = wg == 0 && wk.tail;
#pragma unroll 1
    for (int tile = 1; tile < 4; tile++) {
        wg_wait<0>();
        TL(wg, 11 * tile);
        arrive_cluster_if(rel + 8 * 8, do_rel);
        stage_out<16>(d, zs + 256, ost, w);
        publish(om, ocol, 128 * (tile - 1));
        TL(wg, 1 + 11 * tile);
        if (tile == 3 && wk.tail) {
            if (wg == 0) break;
            asm volatile("bar.sync 6, 256;" ::: "memory");
        }
        const bool rel_lo = do_rel && (tile < 3 || wk.tail), rel_hi = do_rel && tile < 3;
        static_for<0, 9>([&](auto kb_) {
            constexpr int kb = decltype(kb_)::value;
            mbar_wait(full + 8 * kb, tile & 1);
            TLB(wg, 2 + 11 * tile + kb);
            mma_block<kb, false, true>(d, a, dbase + ((tile + 1u) << 16));
            if constexpr (kb == 6) staging_free();
            if constexpr (kb > 0) { wg_wait<1>(); arrive_cluster_if(rel + 8 * (kb - 1), kb - 1 <= tail_stage(8) ? rel_lo : rel_hi); }
        });
    }
    DqState q;
    if (tail) {
        CWAIT(full, 1);
        static_for<0, 9>([&](auto kb_) {
            constexpr int kb = decltype(kb_)::value;
            TLB(wg, 35 + kb);
            mma_block<kb, false, true>(d, a, dbase + (4u << 16));
            if constexpr (kb == T3_UNTIL) asm volatile("bar.arrive 6, 256;" ::: "memory");
            if constexpr (kb < 8) CWAIT(full + 8 * (kb + 1), 1);
            if constexpr (kb == 0) {
                const int l2 = fresh_lane();
                dq_setup<2, DQB_SHF>(q, sb + WS + w * (57 * 64), wk.jb, l2 >> 2, l2 & 3);
                CWAIT(sb + WFULL, 1);
                q.z0 = lds32(zs + 512 + (l2 & ~3));
            }
            if constexpr (kb == 6) staging_free();
            if constexpr (kb >= 2) dq_load<2, kb - 2>(a, q);
            if constexpr (kb > 0) {
                wg_wait<1>();
                if constexpr (kb - 1 <= tail_stage(8)) arrive_cluster_if(rel + 8 * (kb - 1), do_rel);
            }
        });
    }
    wg_wait<0>();
    TL(wg, 44);
    stage_out<16>(d, zs + 256, ost, w);
    publish(om, ocol, 384);
    TL(wg, 45);

    if (tail) {
        dq_zero<FAST>(q, q.z0);
        dq_load<2, 7>(a, q);
        dq_load<2, 8>(a, q);
        dq_conv<FAST, DQB_SHF, 0, S0>(a, q);
        CWAIT(sb + TFULL, 0);
        static_for<0, 9>([&](auto kb_) {
            constexpr int kb = decltype(kb_)::value;
            TLB(wg, 46 + kb);
            mma_block<kb, true, true>(d, a, dbase + (5u << 16));
            if constexpr (kb < 8) CWAIT(sb + TFULL + 8 * (kb + 1), 0);
            if constexpr (S0 + 2 * kb < 36) dq_conv<FAST, DQB_SHF, S0 + 2 * kb, S0 + 2 * kb + 2>(a, q);
            if constexpr (kb == 6 && !DIRECT) staging_free();
        });
        cluster_arrive();
        wg_wait<0>();
        TL(wg, 55);
        direct_out(d, zs + 640, outp, wk.fb, wk.jb, wk.rb, w);
        TL(wg, 56);
    } else {
        cluster_arrive();
    }
    if (storer) {
        asm volatile("mbarrier.arrive.shared::cta.b64 _, [%0];" :: "r"(sb + DONE) : "memory");
        tma_st_wait_read();
    }
    cluster_wait();
    TL(wg, 57);
    TG(wg, 58);
    TDUMP(wg);
}

__global__ void __cluster_dims__(2, 1, 1) __launch_bounds__(384, 1)
gptq_kernel(const __grid_constant__ CUtensorMap xm, const __grid_constant__ CUtensorMap xt,
            const __grid_constant__ CUtensorMap om, const __grid_constant__ CUtensorMap ot,
            const __grid_constant__ CUtensorMap wm, const __grid_constant__ CUtensorMap wt,
            const uint32_t* __restrict__ scales2, const uint32_t* __restrict__ zeros2,
            const char* __restrict__ xg, const char* __restrict__ wg_ptr, char* __restrict__ outp) {
    extern __shared__ __align__(1024) uint8_t smem[];
    const uint32_t sb = (uint32_t)__cvta_generic_to_shared(smem);
    const int warp = __shfl_sync(0xffffffffu, threadIdx.x >> 5, 0);
    const int lane = threadIdx.x & 31;
    const int rank = blockIdx.x & 1, c = blockIdx.x >> 1;
    Work wk;
    wk.ja = c & 3;
    wk.fa = ((c >> 2) * 2 + rank) * 128;
    const int ut = (c * 52) >> 8;
    wk.tail = c < 60;
    wk.jb = ut < 4 ? 2 + (ut & 1) : (ut & 3);
    wk.fb = (ut < 4 ? 32 + (ut >> 1) : 33 + (ut >> 2)) * 128 + 64 * rank;
    wk.rb = (c - 5 * ut) * kTailN;

    const int xc = kXJ * wk.ja;
    if (warp >= 10) {
        const int ci = (c >> 2) * 2 + rank;
        if (warp == 10) {
            const char* xr = xg + (size_t)(4 * ci + (lane & 3)) * 4560 + 1136 * wk.ja;
            if (ci < 32 && lane < (PREF == 1 ? 12 : 20)) pf_l2(xr + (lane >> 2) * 128);
        } else {
            const char* wr = wg_ptr + (size_t)(wk.ja + 4 * (lane >> 2)) * (4 * kF) + wk.fa * 4 + (lane & 3) * 128;
            if (lane < (PREF == 2 ? 32 : 16)) pf_l2(wr);
        }
    }
    if (warp < 10 && elect_one()) {
        const uint32_t b = sb + BARS + 8 * warp;
        mbar_init(warp < 9 ? b : sb + WFULL, 1);
        mbar_init(warp < 9 ? b + 72 : sb + DONE + 8, 1);
        mbar_init(warp < 9 ? b + 144 : sb + DONE, warp < 9 ? 4 : 2);
        asm volatile("fence.mbarrier_init.release.cluster;" ::: "memory");
    }
    __syncwarp();
    cluster_arrive();
    if (warp == 9 && elect_one()) {
        TL1(2, 61);
        w_piece(sb + WS, &wm, wk.fa, 0, sb + WFULL);
        bulk_ld(sb + ZS, zeros2 + wk.fa / 2, 256, sb + WFULL);
        bulk_ld(sb + ZS + 256, scales2 + wk.fa / 2, 256, sb + WFULL);
        mbar_expect(sb + WFULL, kPiece + 512);
        TL1(2, 60);
    }
    if (warp == 8 && elect_one()) prefetch_map(&xm);
    __syncwarp();
    cluster_wait();
    if (warp == 8 && elect_one()) {
        TL1(2, 8);
        tma_ld_mc(sb + XS + rank * (kStage / 2), &xm, xc, 64 * rank, sb + FULL);
        w_piece(sb + WS + kPiece, &wm, wk.fa, 8, sb + FULL);
        TL1(2, 1);
    }
    if (warp == 10 && elect_one()) {
#pragma unroll
        for (int i = 0; i < 9; i++) mbar_expect(sb + FULL + 8 * i, i < 7 ? kStage + kPiece : kStage);
    }
    __syncwarp();

    if (warp >= 8) {
        asm volatile("setmaxnreg.dec.sync.aligned.u32 24;");
        if (!elect_one()) return;
        if (warp == 8) {
            TG1(2, 10);
            {
#pragma unroll 1
                for (int kb = 1; kb < 9; kb++) {
                    if (WINDOW > 0 && kb >= WINDOW) mbar_wait(sb + FULL + 8 * (kb - WINDOW), 0);
                    TLB1(2, 11 + kb);
                    tma_ld_mc(sb + XS + kb * kStage + rank * (kStage / 2), &xm, xc + 64 * kb, 64 * rank, sb + FULL + 8 * kb);
                    if (kb < 7) w_piece(sb + WS + (kb + 1) * kPiece, &wm, wk.fa, 8 * (kb + 1), T0MODE == 2 ? sb + FULL + 8 * kb : sb + WFULL + 8 + 8 * kb);
                }
                prefetch_map(&om); prefetch_map(&xt); prefetch_map(&ot); prefetch_map(&wt);
                const int tc = kXJ * wk.jb, tr = wk.rb + (kTailN - kTailBox) * rank;
                const uint32_t tdst = sb + XT + rank * ((kTailN - kTailBox) * 128);
#pragma unroll 1
                for (int tile = 1; tile < 4; tile++) {
#pragma unroll 1
                    for (int kb = 0; kb < 9; kb++) {
                        mbar_wait(sb + EMPTY + 8 * kb, (tile - 1) & 1);
                        TLB1(2, 11 + 9 * tile + kb);
                        mbar_expect(sb + FULL + 8 * kb, kStage);
                        tma_ld_mc(sb + XS + kb * kStage + rank * (kStage / 2), &xm, xc + 64 * kb,
                                  128 * tile + 64 * rank, sb + FULL + 8 * kb);
                        if (tile == 2 && kb == 0 && wk.tail) {
                            mbar_expect(sb + WFULL, 57 * 256 + 256);
                            tma_ld3(sb + WS, &wt, 0, wk.fb >> 4, sb + WFULL);
                            bulk_ld(sb + ZS + 512, zeros2 + wk.fb / 2, 128, sb + WFULL);
                            bulk_ld(sb + ZS + 640, scales2 + wk.fb / 2, 128, sb + WFULL);
                        }
                        if (tile == 2 && kb == 4 && wk.tail) {
                            mbar_expect(sb + TFULL, 2 * kTailBox * 128);
                            tma_ld_mc(tdst, &xt, tc, tr, sb + TFULL);
                        }
                    }
                }
                if (wk.tail) {
                    static_for<1, 9>([&](auto kb_) {
                        constexpr int kb = decltype(kb_)::value;
                        if constexpr (kb == 1 || tail_stage(kb) != tail_stage(kb - 1)) mbar_wait(sb + EMPTY + 8 * tail_stage(kb), 1);
                        mbar_expect(sb + TFULL + 8 * kb, 2 * kTailBox * 128);
                        tma_ld_mc(tdst + kb * kTailBlk, &xt, tc + 64 * kb, tr, sb + TFULL + 8 * kb);
                    });
                }
            }
            TL1(2, 2);
            TDUMP1(2);
        } else if (warp == 9) {
            int n = 0;
            while (!mbar_try(sb + DONE, 0)) { if (++n > (1 << 20)) __trap(); }
        }
    } else {
        asm volatile("setmaxnreg.inc.sync.aligned.u32 240;");
        consumer<true>(sb, wk, warp >> 2, warp & 3, lane, &om, &ot, outp);
    }
}

typedef CUresult (*EncodeFn)(CUtensorMap*, CUtensorMapDataType, cuuint32_t, void*, const cuuint64_t*, const cuuint64_t*,
                             const cuuint32_t*, const cuuint32_t*, CUtensorMapInterleave, CUtensorMapSwizzle,
                             CUtensorMapL2promotion, CUtensorMapFloatOOBfill);

void make_map(EncodeFn enc, CUtensorMap* m, CUtensorMapDataType dt, const void* p, uint64_t d0, uint64_t d1,
              uint64_t stride, uint32_t b0, uint32_t b1, CUtensorMapSwizzle sw, CUtensorMapL2promotion promo) {
    cuuint64_t gd[2] = {d0, d1}, gs[1] = {stride};
    cuuint32_t bx[2] = {b0, b1}, es[2] = {1, 1};
    enc(m, dt, 2, const_cast<void*>(p), gd, gs, bx, es, CU_TENSOR_MAP_INTERLEAVE_NONE, sw, promo,
        CU_TENSOR_MAP_FLOAT_OOB_FILL_NONE);
}

void make_wmap(EncodeFn enc, CUtensorMap* m, const void* p, uint32_t rows, uint32_t groups) {
    cuuint64_t gd[3] = {16, 57, 288}, gs[2] = {4 * kF, 64};
    cuuint32_t bx[3] = {16, rows, groups}, es[3] = {1, 1, 1};
    enc(m, CU_TENSOR_MAP_DATA_TYPE_INT32, 3, const_cast<void*>(p), gd, gs, bx, es, CU_TENSOR_MAP_INTERLEAVE_NONE,
        CU_TENSOR_MAP_SWIZZLE_NONE, CU_TENSOR_MAP_L2_PROMOTION_L2_128B, CU_TENSOR_MAP_FLOAT_OOB_FILL_NONE);
}

}

extern "C" void kernel_launch(void* const* d_in, const int* in_sizes, int n_in, void* d_out, int out_size) {
    static EncodeFn enc = nullptr;
    if (!enc) {
        void* fn = nullptr;
        cudaDriverEntryPointQueryResult qr;
        cudaGetDriverEntryPoint("cuTensorMapEncodeTiled", &fn, cudaEnableDefault, &qr);
        enc = (EncodeFn)fn;
        cudaFuncSetAttribute(gptq_kernel, cudaFuncAttributeMaxDynamicSharedMemorySize, kSmemTot);
    }
    CUtensorMap xm, xt, om, ot, wm, wt;
    const CUtensorMapDataType bf = CU_TENSOR_MAP_DATA_TYPE_BFLOAT16;
    make_map(enc, &xm, bf, d_in[0], 2280, 512, 4560, 64, 64, CU_TENSOR_MAP_SWIZZLE_128B, CU_TENSOR_MAP_L2_PROMOTION_L2_128B);
    make_map(enc, &xt, bf, d_in[0], 2280, 512, 4560, 64, kTailBox, CU_TENSOR_MAP_SWIZZLE_128B, CU_TENSOR_MAP_L2_PROMOTION_L2_128B);
    make_map(enc, &om, bf, d_out, 4 * kF, 512, 8 * kF, 64, 128, CU_TENSOR_MAP_SWIZZLE_128B, CU_TENSOR_MAP_L2_PROMOTION_NONE);
    make_map(enc, &ot, bf, d_out, 4 * kF, 512, 8 * kF, 64, kTailN, CU_TENSOR_MAP_SWIZZLE_128B, CU_TENSOR_MAP_L2_PROMOTION_NONE);
    make_map(enc, &wm, CU_TENSOR_MAP_DATA_TYPE_INT32, d_in[1], kF, 57, 4 * kF, 128, 8, CU_TENSOR_MAP_SWIZZLE_NONE, CU_TENSOR_MAP_L2_PROMOTION_L2_128B);
    if (LAYA) make_wmap(enc, &wm, d_in[1], 8, 8);
    make_wmap(enc, &wt, d_in[1], 57, 4);
    gptq_kernel<<<132, 384, kSmemTot, cudaStreamPerThread>>>(xm, xt, om, ot, wm, wt, (const uint32_t*)d_in[2], (const uint32_t*)d_in[3],
                                                          (const char*)d_in[0], (const char*)d_in[1], (char*)d_out);
}
```

```cpp
#include <cuda_runtime.h>
#include <cuda_bf16.h>
#include <cuda.h>
#include <stdint.h>
#include <type_traits>

#define DEV __device__ __forceinline__

namespace {

constexpr int      kF        = 4608;
constexpr int      kXJ       = 568;
constexpr uint32_t kStage    = 16384;
constexpr int      kTailN    = 104;
constexpr int      kTailBox  = 56;
constexpr uint32_t kTailBlk  = kTailN * 128;
constexpr uint32_t kPiece    = 8 * 512;
constexpr uint32_t X7        = 0;
constexpr uint32_t XS        = 17 * 1024;
constexpr uint32_t OS        = XS + 9 * kStage;
constexpr uint32_t WS        = OS + 2 * kStage;
constexpr uint32_t X8        = WS + 4 * kPiece;
constexpr uint32_t ZS        = WS + 8 * kPiece;
constexpr uint32_t BARS      = ZS + 768;
constexpr uint32_t FULL      = BARS;
constexpr uint32_t TFULL     = BARS + 72;
constexpr uint32_t EMPTY     = BARS + 144;
constexpr uint32_t WFULL     = BARS + 216;
constexpr uint32_t DONE      = BARS + 224;
constexpr uint32_t ZCHK      = BARS + 232;
constexpr uint32_t XFULL     = BARS + 256;
constexpr uint32_t kSmem     = BARS + 272;
__host__ __device__ constexpr uint32_t tail_off(int i) { return i < 2 ? XS + 7 * kStage + i * kTailBlk : XS + (i - 2) * kTailBlk; }
__host__ __device__ constexpr int tail_stage(int i) { return ((i - 1) * (int)kTailBlk - 1) / (int)kStage; }
__host__ __device__ constexpr int t3_delta(int kb) { return kb < 7 ? 0 : ((int)(kb == 7 ? X7 : X8) - (int)(XS + kb * kStage)) / 16; }
constexpr int kPauseAt = 6, kPauseUntil = 8;
constexpr int kSplit   = 2;
constexpr int kWindow  = 3;
constexpr int kBurst   = 20;

DEV void mbar_init(uint32_t a, uint32_t c) { asm volatile("mbarrier.init.shared::cta.b64 [%0], %1;" :: "r"(a), "r"(c) : "memory"); }
DEV void mbar_expect(uint32_t a, uint32_t tx) { asm volatile("mbarrier.arrive.expect_tx.shared::cta.b64 _, [%0], %1;" :: "r"(a), "r"(tx) : "memory"); }
DEV void mbar_arrive(uint32_t a) { asm volatile("mbarrier.arrive.shared::cta.b64 _, [%0];" :: "r"(a) : "memory"); }
DEV void mbar_wait(uint32_t a, uint32_t par) {
    asm volatile("{\n.reg .pred p;\nL:\nmbarrier.try_wait.parity.shared::cta.b64 p, [%0], %1;\n@!p bra.uni L;\n}"
                 :: "r"(a), "r"(par) : "memory");
}
DEV void mbar_spin(uint32_t a, uint32_t par) {
    asm volatile("{\n.reg .pred p;\nL:\nmbarrier.test_wait.parity.shared::cta.b64 p, [%0], %1;\n@!p bra.uni L;\n}"
                 :: "r"(a), "r"(par) : "memory");
}
DEV bool mbar_try(uint32_t a, uint32_t par) {
    uint32_t ok;
    asm volatile("{\n.reg .pred p;\nmbarrier.try_wait.parity.shared::cta.b64 p, [%1], %2;\nselp.u32 %0, 1, 0, p;\n}"
                 : "=r"(ok) : "r"(a), "r"(par) : "memory");
    return ok;
}
DEV void arrive_cluster_if(uint32_t a, bool p) {
    asm volatile("{\n.reg .pred p;\nsetp.ne.b32 p, %1, 0;\n@p mbarrier.arrive.shared::cluster.b64 _, [%0];\n}"
                 :: "r"(a), "r"((uint32_t)p) : "memory");
}
DEV void tma_ld_w(uint32_t dst, const CUtensorMap* m, int f, int row, uint32_t bar) {
    asm volatile("cp.async.bulk.tensor.3d.shared::cluster.global.mbarrier::complete_tx::bytes [%0], [%1, {0, %3, %4}], [%2];"
                 :: "r"(dst), "l"(m), "r"(bar), "r"(row), "r"(f >> 4) : "memory");
}
DEV void tma_ld_x(uint32_t dst, const CUtensorMap* m, int c0, int c1, uint32_t bar) {
    asm volatile("cp.async.bulk.tensor.2d.shared::cluster.global.mbarrier::complete_tx::bytes.multicast::cluster [%0], [%1, {%3, %4}], [%2], %5;"
                 :: "r"(dst), "l"(m), "r"(bar), "r"(c0), "r"(c1), "h"((uint16_t)3) : "memory");
}
DEV void bulk_ld(uint32_t dst, const void* src, uint32_t bytes, uint32_t bar) {
    asm volatile("cp.async.bulk.shared::cluster.global.mbarrier::complete_tx::bytes [%0], [%1], %2, [%3];"
                 :: "r"(dst), "l"(src), "r"(bytes), "r"(bar) : "memory");
}
DEV void tma_st(const CUtensorMap* m, int c0, int c1, uint32_t src) {
    asm volatile("cp.async.bulk.tensor.2d.global.shared::cta.bulk_group [%0, {%2, %3}], [%1];"
                 :: "l"(m), "r"(src), "r"(c0), "r"(c1) : "memory");
    asm volatile("cp.async.bulk.commit_group;" ::: "memory");
}
DEV void tma_st_wait_read() { asm volatile("cp.async.bulk.wait_group.read 0;" ::: "memory"); }
DEV uint32_t lds32(uint32_t a) { uint32_t v; asm volatile("ld.shared.b32 %0, [%1];" : "=r"(v) : "r"(a)); return v; }
DEV bool elect_one() {
    uint32_t p;
    asm volatile("{\n.reg .pred p;\nelect.sync _|p, 0xffffffff;\nselp.u32 %0, 1, 0, p;\n}" : "=r"(p));
    return p;
}
DEV int fresh_lane() { int v; asm volatile("mov.u32 %0, %%laneid;" : "=r"(v)); return v; }
DEV void prefetch_l2(const void* p) { asm volatile("prefetch.global.L2 [%0];" :: "l"(p)); }
DEV void prefetch_map(const CUtensorMap* m) { asm volatile("prefetch.tensormap [%0];" :: "l"(m) : "memory"); }
DEV void bar_sync(int id) { asm volatile("bar.sync %0, 128;" :: "r"(id) : "memory"); }
template <int ID> DEV void order_wait() { asm volatile("bar.sync %0, 256;" :: "n"(ID) : "memory"); }
template <int ID> DEV void order_signal() { asm volatile("bar.arrive %0, 256;" :: "n"(ID) : "memory"); }
DEV void wg_fence() { asm volatile("wgmma.fence.sync.aligned;" ::: "memory"); }
DEV void wg_commit() { asm volatile("wgmma.commit_group.sync.aligned;" ::: "memory"); }
template <int N> DEV void wg_wait() { asm volatile("wgmma.wait_group.sync.aligned %0;" :: "n"(N) : "memory"); }
DEV uint32_t bf2_add(uint32_t a, uint32_t b) { uint32_t d; asm("add.rn.bf16x2 %0, %1, %2;" : "=r"(d) : "r"(a), "r"(b)); return d; }
DEV uint32_t bf2_sub(uint32_t a, uint32_t b) { uint32_t d; asm("sub.rn.bf16x2 %0, %1, %2;" : "=r"(d) : "r"(a), "r"(b)); return d; }
DEV uint32_t pack_scaled(float lo, float hi, uint32_t spair) {
    uint32_t p;
    asm("cvt.rn.bf16x2.f32 %0, %1, %2;" : "=r"(p) : "f"(hi), "f"(lo));
    asm("mul.rn.bf16x2 %0, %0, %1;" : "+r"(p) : "r"(spair));
    return p;
}
template <int I, int N, typename F>
DEV void static_for(F&& f) {
    if constexpr (I < N) { f(std::integral_constant<int, I>{}); static_for<I + 1, N>(f); }
}

#define ACC8(d, o) "+f"(d[o + 0]), "+f"(d[o + 1]), "+f"(d[o + 2]), "+f"(d[o + 3]), "+f"(d[o + 4]), "+f"(d[o + 5]), "+f"(d[o + 6]), "+f"(d[o + 7])

template <int ACCUM>
DEV void wgmma_n128(float (&d)[64], uint32_t a0, uint32_t a1, uint32_t a2, uint32_t a3, uint64_t desc) {
    asm volatile(
        "wgmma.mma_async.sync.aligned.m64n128k16.f32.bf16.bf16 "
        "{%0,%1,%2,%3,%4,%5,%6,%7,%8,%9,%10,%11,%12,%13,%14,%15,%16,%17,%18,%19,%20,%21,%22,%23,%24,%25,%26,%27,%28,%29,%30,%31,"
        "%32,%33,%34,%35,%36,%37,%38,%39,%40,%41,%42,%43,%44,%45,%46,%47,%48,%49,%50,%51,%52,%53,%54,%55,%56,%57,%58,%59,%60,%61,%62,%63},"
        "{%64,%65,%66,%67}, %68, %69, 1, 1, 0;\n"
        : ACC8(d, 0), ACC8(d, 8), ACC8(d, 16), ACC8(d, 24), ACC8(d, 32), ACC8(d, 40), ACC8(d, 48), ACC8(d, 56)
        : "r"(a0), "r"(a1), "r"(a2), "r"(a3), "l"(desc), "n"(ACCUM));
}
template <int ACCUM>
DEV void wgmma_n104(float (&d)[64], uint32_t a0, uint32_t a1, uint32_t a2, uint32_t a3, uint64_t desc) {
    asm volatile(
        "wgmma.mma_async.sync.aligned.m64n104k16.f32.bf16.bf16 "
        "{%0,%1,%2,%3,%4,%5,%6,%7,%8,%9,%10,%11,%12,%13,%14,%15,%16,%17,%18,%19,%20,%21,%22,%23,%24,%25,%26,%27,%28,%29,%30,%31,"
        "%32,%33,%34,%35,%36,%37,%38,%39,%40,%41,%42,%43,%44,%45,%46,%47,%48,%49,%50,%51},"
        "{%52,%53,%54,%55}, %56, %57, 1, 1, 0;\n"
        : ACC8(d, 0), ACC8(d, 8), ACC8(d, 16), ACC8(d, 24), ACC8(d, 32), ACC8(d, 40),
          "+f"(d[48]), "+f"(d[49]), "+f"(d[50]), "+f"(d[51])
        : "r"(a0), "r"(a1), "r"(a2), "r"(a3), "l"(desc), "n"(ACCUM));
}

template <int KB, bool TAIL>
DEV void mma_block(float (&d)[64], const uint32_t (&a)[144], uint64_t dbase) {
    constexpr uint32_t off = TAIL ? tail_off(KB) : XS + KB * kStage;
    wg_fence();
#pragma unroll
    for (int kk = 0; kk < 4; kk++) {
        const int s = 16 * KB + 4 * kk;
        const uint64_t desc = dbase + (off >> 4) + 2 * kk;
        if (KB == 0 && kk == 0) {
            if (TAIL) wgmma_n104<0>(d, a[s], a[s + 1], a[s + 2], a[s + 3], desc);
            else      wgmma_n128<0>(d, a[s], a[s + 1], a[s + 2], a[s + 3], desc);
        } else {
            if (TAIL) wgmma_n104<1>(d, a[s], a[s + 1], a[s + 2], a[s + 3], desc);
            else      wgmma_n128<1>(d, a[s], a[s + 1], a[s + 2], a[s + 3], desc);
        }
    }
    wg_commit();
}

constexpr uint32_t kMagic = 0x41004280u;
struct DqState {
    uint32_t addr[5];
    uint32_t addr0;
    uint32_t mul[5];
    uint32_t z0, z1;
    uint32_t magic;
    int j;
};

DEV void dq_setup(DqState& q, uint32_t slab, int j, int lane) {
    const int e = (lane & 3) - j;
#pragma unroll
    for (int r = 0; r < 5; r++) {
        const int n = 4 * r + e + 5;
        const int w = (n * 52) >> 8;
        q.addr[r] = slab + (w - 1) * 64 + (lane >> 2) * 8;
        asm("shl.b32 %0, 1, %1;" : "=r"(q.mul[r]) : "r"(25 - 6 * (n - 5 * w)));
    }
    q.addr0 = q.addr[0] - (e < 0 ? 4096 - 512 : 0);
    q.j = j;
    q.magic = kMagic;
}
DEV void dq_zero(DqState& q, uint32_t zpair) {
    q.z0 = bf2_add(__byte_perm(zpair, 0, 0x1010), kMagic);
    q.z1 = bf2_add(__byte_perm(zpair, 0, 0x3232), kMagic);
}
DEV bool zero_exact(uint32_t zpair) {
    const uint32_t z0 = __byte_perm(zpair, 0, 0x1010), z1 = __byte_perm(zpair, 0, 0x3232);
    return bf2_sub(bf2_add(z0, kMagic), kMagic) == bf2_add(z0, 0) && bf2_sub(bf2_add(z1, kMagic), kMagic) == bf2_add(z1, 0);
}
DEV uint32_t dq_pair(uint32_t w, uint32_t mul, uint32_t z, uint32_t magic) {
    uint32_t y;
    asm("mul.lo.u32 %0, %1, %2;" : "=r"(y) : "r"(w), "r"(mul));
    y = __byte_perm(y, 0, 0x3333);
    asm("lop3.b32 %0, %1, 0x0070000E, %2, 0xEA;" : "=r"(y) : "r"(y), "r"(magic));
    return bf2_sub(y, z);
}
template <bool TAIL, int KB>
DEV void dq_load(uint32_t (&a)[144], const DqState& q) {
#pragma unroll
    for (int u = 8 * KB; u < 8 * KB + 8; u++) {
        const int v = u / 5, r = u % 5;
        const uint32_t addr = TAIL ? q.addr[r] + 256 * v
                                   : ((r == 0 && !(v & 1) && v > 0) ? q.addr0 : q.addr[r]) + 4096 * (v >> 1) + 256 * (v & 1);
        asm volatile("ld.shared.v2.b32 {%0, %1}, [%2];" : "=r"(a[2 * u]), "=r"(a[2 * u + 1]) : "r"(addr));
    }
}
template <int SA, int SB>
DEV void dq_conv(uint32_t (&a)[144], const DqState& q) {
#pragma unroll
    for (int u = 2 * SA; u < 2 * SB; u++) {
        uint32_t x0 = dq_pair(a[2 * u], q.mul[u % 5], q.z0, q.magic);
        uint32_t x1 = dq_pair(a[2 * u + 1], q.mul[u % 5], q.z1, q.magic);
        if (u == 0 || u == 71) {
            const int t = fresh_lane() & 3;
            const bool ok = (u == 0) ? (t >= q.j) : (t <= q.j);
            x0 = ok ? x0 : 0u;
            x1 = ok ? x1 : 0u;
        }
        a[2 * u] = x0;
        a[2 * u + 1] = x1;
    }
}

template <typename F>
DEV void stage_out(const float (&d)[64], uint32_t sbase, uint32_t ost, int w, F&& after_wait) {
    const int lane = fresh_lane(), g = lane >> 2, t = lane & 3;
    const uint32_t spair = lds32(sbase + 4 * g);
    const uint32_t o0 = ost + (2 * t) * 128 + (((2 * w + (g >> 2)) ^ (2 * t)) << 4) + 4 * (g & 3);
    const uint32_t o1 = (o0 ^ 16) + 128;
    wg_wait<0>();
    after_wait();
#pragma unroll
    for (int c = 0; c < 16; c++) {
        const uint32_t p0 = pack_scaled(d[4 * c + 0], d[4 * c + 2], spair);
        const uint32_t p1 = pack_scaled(d[4 * c + 1], d[4 * c + 3], spair);
        asm volatile("st.shared.b32 [%0], %1;" :: "r"(o0 + 1024 * c), "r"(p0) : "memory");
        asm volatile("st.shared.b32 [%0], %1;" :: "r"(o1 + 1024 * c), "r"(p1) : "memory");
    }
}
DEV void direct_out(const float (&d)[64], uint32_t sbase, char* out, int col, int cls, int row0, int w) {
    const int lane = fresh_lane(), g = lane >> 2, t = lane & 3;
    const uint32_t spair = lds32(sbase + 4 * g);
    char* p = out + (size_t)(4 * (row0 + 2 * t) + cls) * (2 * kF) + (col + 16 * w + 2 * g) * 2;
    wg_wait<0>();
#pragma unroll
    for (int c = 0; c < kTailN / 8; c++) {
        const uint32_t p0 = pack_scaled(d[4 * c + 0], d[4 * c + 2], spair);
        const uint32_t p1 = pack_scaled(d[4 * c + 1], d[4 * c + 3], spair);
        if (c < kTailN / 8 - 1 || row0 + kTailN <= 512) {
            *(uint32_t*)(p + (size_t)c * (64 * kF)) = p0;
            *(uint32_t*)(p + (size_t)c * (64 * kF) + 8 * kF) = p1;
        }
    }
}

struct Work { int ja, fa, jb, fb, rb; bool tail; };
DEV void tail_work(Work& wk) {
    int b;
    asm volatile("mov.u32 %0, %%ctaid.x;" : "=r"(b));
    const int c = b >> 1, ut = (c * 52) >> 8;
    wk.tail = c < 60;
    wk.jb = ut < 4 ? 2 + (ut & 1) : (ut & 3);
    wk.fb = wk.tail ? (ut < 4 ? 32 + (ut >> 1) : 33 + (ut >> 2)) * 128 + 64 * (b & 1) : 0;
    wk.rb = (c - 5 * ut) * kTailN;
}

struct Ptrs { const uint16_t* x; const uint32_t* w; const uint16_t* s; const uint16_t* z; __nv_bfloat16* out; };
__device__ __noinline__ void fixup(const Ptrs p, int f0, int cls, int row0, int rows) {
    const int f = f0 + (threadIdx.x & 63);
    const uint32_t zr = p.z[f];
    if (zero_exact(zr | (zr << 16))) return;
    const float z = __uint_as_float(zr << 16), s = __uint_as_float((uint32_t)p.s[f] << 16);
    for (int i = row0 + ((threadIdx.x >> 6) & 1); i < row0 + rows && i < 512; i += 2) {
        const int m = 4 * i + cls;
        float acc = 0.f;
        for (int r = 0; r < 57; r++) {
            const uint32_t word = p.w[r * kF + f];
#pragma unroll 1
            for (int e = 0; e < 10; e++) {
                const float dq = __bfloat162float(__float2bfloat16_rn((float)((word >> (3 * e)) & 7) - z));
                const float wv = __bfloat162float(__float2bfloat16_rn(dq * s));
                acc = fmaf(__uint_as_float((uint32_t)p.x[m * 570 + 10 * r + e] << 16), wv, acc);
            }
        }
        p.out[(size_t)m * kF + f] = __float2bfloat16_rn(acc);
    }
}

DEV void consumer(const uint32_t sb, const Work wk, const int wg, const int w, const int lane,
                  const CUtensorMap* om, const Ptrs& ptrs, DqState& q) {
    const uint32_t full = sb + FULL;
    uint32_t rel;
    asm("mapa.shared::cluster.u32 %0, %1, %2;" : "=r"(rel) : "r"(sb + EMPTY), "r"(w & 1));
    const bool do_rel = (lane == 0) && (w < 2);
    const bool storer = (lane == 0) && (w == 3);
    const uint32_t ost = sb + OS + wg * kStage;
    const uint64_t dbase = (uint64_t)((sb & 0x3FFFF) >> 4) | (64ull << 32) | (1ull << 62);
    const uint32_t zs = sb + ZS + 128 * wg + 32 * w;
    const int ocol = wk.ja * kF + wk.fa + wg * 64;

    uint32_t a[144];
    float d[64];

    auto publish = [&](int row) {
        asm volatile("fence.proxy.async.shared::cta;" ::: "memory");
        bar_sync(1 + wg);
        if (storer) tma_st(om, ocol, row, ost);
    };
    auto staging_free = [&]() {
        if (storer) tma_st_wait_read();
        bar_sync(3 + wg);
    };

    const uint32_t sel = 0x3210u + (uint32_t)((size_t)ptrs.out & 1);
    mbar_wait(sb + WFULL, 0);
    dq_zero(q, lds32(zs + (lane & ~3)));
    dq_load<false, 0>(a, q);
    dq_conv<0, 4>(a, q);
    static_for<0, 9>([&](auto kb_) {
        constexpr int kb = decltype(kb_)::value;
        if constexpr (kb == kPauseAt) { if (wg == 1) order_wait<5>(); }
        mbar_spin(full + 8 * kb, 0);
        if constexpr (kb < 8) dq_load<false, kb + 1>(a, q);
        mma_block<kb, false>(d, a, dbase + (1u << 16));
        if constexpr (kb < 8) dq_conv<4 * kb + 4, 4 * kb + 4 + kSplit>(a, q);
        if constexpr (kb == kPauseUntil) { if (wg == 0) order_signal<5>(); }
        if constexpr (kb > 0) { wg_wait<1>(); arrive_cluster_if(rel + 8 * (kb - 1), do_rel); }
        if constexpr (kb < 8) {
            uint32_t c;
            asm volatile("mov.u32 %0, %%clock;" : "=r"(c) :: "memory");
            q.magic = __byte_perm(kMagic, c, sel);
            dq_conv<4 * kb + 4 + kSplit, 4 * kb + 8>(a, q);
        }
    });

    const bool tail = wg == 0 && wk.tail;
#pragma unroll 1
    for (int tile = 1; tile < 4; tile++) {
        stage_out(d, zs + 256, ost, w, [&] { arrive_cluster_if(rel + 8 * 8, do_rel && (tile < 3 || wk.tail)); });
        const bool defer = !(tile == 3 && wk.tail);
        if (!defer) {
            publish(256);
            if (wg == 0) break;
            order_wait<6>();
        }
        const bool rel_lo = do_rel && (tile < 3 || wk.tail), rel_hi = do_rel && tile < 3;
        const bool rel_7 = rel_hi && (tile < 2 || wk.tail);
        static_for<0, 9>([&](auto kb_) {
            constexpr int kb = decltype(kb_)::value;
            if constexpr (kb >= 7) {
                const bool t3 = tile == 3;
                mbar_wait(t3 ? sb + XFULL + 8 * (kb - 7) : full + 8 * kb, t3 ? 0 : tile & 1);
                mma_block<kb, false>(d, a, dbase + ((tile + 1u) << 16) + (t3 ? t3_delta(kb) : 0));
            } else {
                mbar_wait(full + 8 * kb, tile & 1);
                mma_block<kb, false>(d, a, dbase + ((tile + 1u) << 16));
            }
            if constexpr (kb == 0) { if (defer) publish(128 * (tile - 1)); }
            if constexpr (kb == 6) staging_free();
            if constexpr (kb > 0) {
                wg_wait<1>();
                arrive_cluster_if(rel + 8 * (kb - 1), kb - 1 <= tail_stage(8) ? rel_lo : kb == 8 ? rel_7 : rel_hi);
            }
        });
    }
    if (tail) {
        mbar_spin(full, 1);
        static_for<0, 9>([&](auto kb_) {
            constexpr int kb = decltype(kb_)::value;
            mma_block<kb, false>(d, a, dbase + (4u << 16) + t3_delta(kb));
            if constexpr (kb == 8) order_signal<6>();
            if constexpr (kb < 6) mbar_spin(full + 8 * (kb + 1), 1);
            else if constexpr (kb < 8) mbar_spin(sb + XFULL + 8 * (kb - 6), 0);
            if constexpr (kb == 0) {
                const int l2 = fresh_lane();
                dq_setup(q, sb + WS + w * (57 * 64), wk.jb, l2);
                mbar_spin(sb + WFULL, 1);
                q.z0 = lds32(zs + 512 + (l2 & ~3));
            }
            if constexpr (kb == 6) staging_free();
            if constexpr (kb >= 2) dq_load<true, kb - 2>(a, q);
            if constexpr (kb > 0) {
                wg_wait<1>();
                if constexpr (kb - 1 <= tail_stage(8)) arrive_cluster_if(rel + 8 * (kb - 1), do_rel);
            }
        });
    }
    stage_out(d, zs + 256, ost, w, [] {});
    publish(384);

    if (tail) {
        dq_zero(q, q.z0);
        dq_load<true, 7>(a, q);
        dq_load<true, 8>(a, q);
        dq_conv<0, kBurst>(a, q);
        mbar_spin(sb + TFULL, 0);
        static_for<0, 9>([&](auto kb_) {
            constexpr int kb = decltype(kb_)::value;
            mma_block<kb, true>(d, a, dbase + (5u << 16));
            if constexpr (kb < 8) mbar_spin(sb + TFULL + 8 * (kb + 1), 0);
            if constexpr (kBurst + 2 * kb < 36) dq_conv<kBurst + 2 * kb, kBurst + 2 * kb + 2>(a, q);
        });
        if (storer) mbar_arrive(sb + DONE);
        direct_out(d, zs + 640, (char*)ptrs.out, wk.fb, wk.jb, wk.rb, w);
    }
    if (storer) {
        if (!tail) mbar_arrive(sb + DONE);
        tma_st_wait_read();
    }
    mbar_spin(sb + ZCHK, 0);
    if (__builtin_expect(__shfl_sync(0xffffffffu, lds32(sb + ZCHK + 8), 0), 0)) {
        if (storer) asm volatile("cp.async.bulk.wait_group 0;" ::: "memory");
        asm volatile("fence.proxy.async.global;" ::: "memory");
        __threadfence();
        bar_sync(1 + wg);
        fixup(ptrs, wk.fa + 64 * wg, wk.ja, 0, 512);
        if (tail) fixup(ptrs, wk.fb, wk.jb, wk.rb, kTailN);
    }
}

DEV void producer(const uint32_t sb, const Work wk, const int rank, const CUtensorMap* xm, const CUtensorMap* xt,
                  const CUtensorMap* om, const CUtensorMap* wm, const CUtensorMap* wt,
                  const uint32_t* scales2, const uint32_t* zeros2) {
    const int xc = kXJ * wk.ja;
    const uint32_t xdst = sb + rank * (kStage / 2);
#pragma unroll 1
    for (int kb = 1; kb < 9; kb++) {
        if (kb >= kWindow) mbar_wait(sb + FULL + 8 * (kb - kWindow), 0);
        tma_ld_x(xdst + XS + kb * kStage, xm, xc + 64 * kb, 64 * rank, sb + FULL + 8 * kb);
        if (kb < 7) tma_ld_w(sb + WS + (kb + 1) * kPiece, wm, wk.fa, 8 * (kb + 1), sb + FULL + 8 * kb);
        if (kb == 7) bulk_ld(sb + ZS + 256, scales2 + wk.fa / 2, 256, sb + FULL + 8 * 7);
    }
    prefetch_map(om); prefetch_map(xt); prefetch_map(wt);
#pragma unroll 1
    for (int tile = 1; tile < 4; tile++) {
#pragma unroll 1
        for (int kb = 0; kb < (tile == 3 ? 7 : 9); kb++) {
            mbar_wait(sb + EMPTY + 8 * kb, (tile - 1) & 1);
            mbar_expect(sb + FULL + 8 * kb, kStage);
            tma_ld_x(xdst + XS + kb * kStage, xm, xc + 64 * kb, 128 * tile + 64 * rank, sb + FULL + 8 * kb);
            if (tile == 2) {
                if (kb == 0 && wk.tail) {
                    mbar_expect(sb + WFULL, 57 * 256 + 256);
                    tma_ld_w(sb + WS, wt, wk.fb, 0, sb + WFULL);
                    bulk_ld(sb + ZS + 512, zeros2 + wk.fb / 2, 128, sb + WFULL);
                    bulk_ld(sb + ZS + 640, scales2 + wk.fb / 2, 128, sb + WFULL);
                }
                if (kb == 2 || kb == 5) {
                    const int e = kb == 5;
                    mbar_expect(sb + XFULL + 8 * e, kStage);
                    tma_ld_x(xdst + (e ? X8 : X7), xm, xc + 64 * (7 + e), 384 + 64 * rank, sb + XFULL + 8 * e);
                }
            }
        }
    }
    if (wk.tail) {
        const int tc = kXJ * wk.jb, tr = wk.rb + (kTailN - kTailBox) * rank;
        const uint32_t tdst = sb + rank * ((kTailN - kTailBox) * 128);
#pragma unroll 1
        for (int kb = 0; kb < 9; kb++) {
            if (kb < 2) mbar_wait(sb + EMPTY + 8 * (7 + kb), 0);
            else mbar_wait(sb + EMPTY + 8 * tail_stage(kb), 1);
            mbar_expect(sb + TFULL + 8 * kb, 2 * kTailBox * 128);
            tma_ld_x(tdst + tail_off(kb), xt, tc + 64 * kb, tr, sb + TFULL + 8 * kb);
        }
    }
}

__global__ void __cluster_dims__(2, 1, 1) __launch_bounds__(384, 1)
gptq_kernel(const __grid_constant__ CUtensorMap xm, const __grid_constant__ CUtensorMap xt,
            const __grid_constant__ CUtensorMap om, const __grid_constant__ CUtensorMap wm,
            const __grid_constant__ CUtensorMap wt,
            const uint32_t* __restrict__ scales2, const uint32_t* __restrict__ zeros2,
            const char* __restrict__ xg, const char* __restrict__ wg_ptr, char* __restrict__ outp) {
    extern __shared__ __align__(1024) uint8_t smem[];
    const uint32_t sb = (uint32_t)__cvta_generic_to_shared(smem);
    if ((threadIdx.x >> 5) == 4) {
        const int ci = (blockIdx.x >> 3) * 2 + (blockIdx.x & 1), j = (blockIdx.x >> 1) & 3, l = threadIdx.x & 31;
        const int off = l < 16 ? (j + 4 * (l >> 2)) * (4 * kF) + ci * 512 + (l & 3) * 128
                               : (4 * (ci & 31) + (l & 3)) * 4560 + 1136 * j + ((l >> 2) - 4) * 128;
        prefetch_l2((l < 16 ? wg_ptr : xg) + off);
        prefetch_map(&wm);
        prefetch_map(&xm);
    }
    const int warp = __shfl_sync(0xffffffffu, threadIdx.x >> 5, 0);
    const int lane = threadIdx.x & 31;
    const int rank = blockIdx.x & 1, c = blockIdx.x >> 1;
    Work wk;
    wk.ja = c & 3;
    wk.fa = ((c >> 2) * 2 + rank) * 128;

    if ((warp >= 9 || warp < 3) && elect_one()) {
        if (warp < 3) {
            mbar_init(sb + WFULL + 8 * warp, warp == 1 ? 2 : 1);
            if (warp > 0) mbar_init(sb + XFULL - 8 + 8 * warp, 1);
        } else {
            const uint32_t b = sb + BARS + 72 * (warp - 9), cnt = warp == 11 ? 4 : 1;
#pragma unroll
            for (int i = 0; i < 9; i++) mbar_init(b + 8 * i, cnt);
        }
        asm volatile("fence.mbarrier_init.release.cluster;" ::: "memory");
    }
    __syncwarp();
    asm volatile("barrier.cluster.arrive.relaxed.aligned;" ::: "memory");
    if (warp == 0 && elect_one()) {
        tma_ld_w(sb + WS, &wm, wk.fa, 0, sb + WFULL);
        bulk_ld(sb + ZS, zeros2 + wk.fa / 2, 256, sb + WFULL);
        mbar_expect(sb + WFULL, kPiece + 256);
    }
    __syncwarp();
    asm volatile("barrier.cluster.wait.aligned;" ::: "memory");
    if (warp == 8 && elect_one()) {
        tma_ld_x(sb + XS + rank * (kStage / 2), &xm, kXJ * wk.ja, 64 * rank, sb + FULL);
        tma_ld_w(sb + WS + kPiece, &wm, wk.fa, 8, sb + FULL);
    }
    if (warp == 10 && elect_one()) {
#pragma unroll
        for (int i = 0; i < 9; i++) mbar_expect(sb + FULL + 8 * i, kStage + (i < 7 ? kPiece : i == 7 ? 256 : 0));
    }
    __syncwarp();

    if (warp >= 8) {
        asm volatile("setmaxnreg.dec.sync.aligned.u32 24;");
        if (warp == 11) {
            tail_work(wk);
            mbar_wait(sb + FULL + 8 * 3, 0);
            const bool ok = zero_exact(__ldg(zeros2 + wk.fa / 2 + lane)) && zero_exact(__ldg(zeros2 + wk.fa / 2 + 32 + lane)) &&
                            zero_exact(__ldg(zeros2 + wk.fb / 2 + lane));
            const uint32_t bad = !__all_sync(0xffffffffu, ok);
            if (lane == 0) {
                asm volatile("st.shared.b32 [%0], %1;" :: "r"(sb + ZCHK + 8), "r"(bad) : "memory");
                mbar_arrive(sb + ZCHK);
            }
        }
        if (!elect_one()) return;
        if (warp == 8) {
            tail_work(wk);
            producer(sb, wk, rank, &xm, &xt, &om, &wm, &wt, scales2, zeros2);
        } else if (warp == 9) {
            int n = 0;
            while (!mbar_try(sb + DONE, 0)) { if (++n > (1 << 20)) __trap(); }
        }
    } else {
        tail_work(wk);
        asm volatile("setmaxnreg.inc.sync.aligned.u32 240;");
        DqState q;
        dq_setup(q, sb + WS + warp * 512, wk.ja, lane);
        asm volatile("{\n.reg .pred p;\nsetp.ne.b32 p, %0, 0;\n@p st.shared.v4.b32 [%1], {%2, %3, %4, %5};\n@p st.shared.v4.b32 [%6], {%7, %8, %9, %10};\n}"
                     :: "r"((uint32_t)((size_t)outp & 1)), "r"(q.addr[0]), "r"(q.addr[1]), "r"(q.addr[2]), "r"(q.addr[3]), "r"(q.mul[0]),
                        "r"(q.addr[4]), "r"(q.mul[1]), "r"(q.mul[2]), "r"(q.mul[3]), "r"(q.mul[4]));
        const Ptrs ptrs{(const uint16_t*)xg, (const uint32_t*)wg_ptr, (const uint16_t*)scales2, (const uint16_t*)zeros2, (__nv_bfloat16*)outp};
        consumer(sb, wk, warp >> 2, warp & 3, lane, &om, ptrs, q);
    }
}

typedef CUresult (*EncodeFn)(CUtensorMap*, CUtensorMapDataType, cuuint32_t, void*, const cuuint64_t*, const cuuint64_t*,
                             const cuuint32_t*, const cuuint32_t*, CUtensorMapInterleave, CUtensorMapSwizzle,
                             CUtensorMapL2promotion, CUtensorMapFloatOOBfill);

void make_map(EncodeFn enc, CUtensorMap* m, const void* p, uint64_t cols, uint32_t rows, CUtensorMapL2promotion promo) {
    cuuint64_t gd[2] = {cols, 512}, gs[1] = {2 * cols};
    cuuint32_t bx[2] = {64, rows}, es[2] = {1, 1};
    enc(m, CU_TENSOR_MAP_DATA_TYPE_BFLOAT16, 2, const_cast<void*>(p), gd, gs, bx, es, CU_TENSOR_MAP_INTERLEAVE_NONE,
        CU_TENSOR_MAP_SWIZZLE_128B, promo, CU_TENSOR_MAP_FLOAT_OOB_FILL_NONE);
}
void make_wmap(EncodeFn enc, CUtensorMap* m, const void* p, uint32_t rows, uint32_t groups) {
    cuuint64_t gd[3] = {16, 57, 288}, gs[2] = {4 * kF, 64};
    cuuint32_t bx[3] = {16, rows, groups}, es[3] = {1, 1, 1};
    enc(m, CU_TENSOR_MAP_DATA_TYPE_INT32, 3, const_cast<void*>(p), gd, gs, bx, es, CU_TENSOR_MAP_INTERLEAVE_NONE,
        CU_TENSOR_MAP_SWIZZLE_NONE, CU_TENSOR_MAP_L2_PROMOTION_L2_128B, CU_TENSOR_MAP_FLOAT_OOB_FILL_NONE);
}

}

extern "C" void kernel_launch(void* const* d_in, const int* in_sizes, int n_in, void* d_out, int out_size) {
    static EncodeFn enc = nullptr;
    if (!enc) {
        void* fn = nullptr;
        cudaDriverEntryPointQueryResult qr;
        cudaGetDriverEntryPoint("cuTensorMapEncodeTiled", &fn, cudaEnableDefault, &qr);
        enc = (EncodeFn)fn;
        cudaFuncSetAttribute(gptq_kernel, cudaFuncAttributeMaxDynamicSharedMemorySize, kSmem);
    }
    CUtensorMap xm, xt, om, wm, wt;
    make_map(enc, &xm, d_in[0], 4 * 570, 64, CU_TENSOR_MAP_L2_PROMOTION_L2_128B);
    make_map(enc, &xt, d_in[0], 4 * 570, kTailBox, CU_TENSOR_MAP_L2_PROMOTION_L2_128B);
    make_map(enc, &om, d_out, 4 * kF, 128, CU_TENSOR_MAP_L2_PROMOTION_NONE);
    make_wmap(enc, &wm, d_in[1], 8, 8);
    make_wmap(enc, &wt, d_in[1], 57, 4);
    gptq_kernel<<<132, 384, kSmem, cudaStreamPerThread>>>(xm, xt, om, wm, wt, (const uint32_t*)d_in[2], (const uint32_t*)d_in[3],
                                                       (const char*)d_in[0], (const char*)d_in[1], (char*)d_out);
}
```

```cpp
#include <cuda_runtime.h>
#include <cuda_bf16.h>
#include <cuda.h>
#include <stdint.h>
#include <type_traits>

#define DEV __device__ __forceinline__

namespace {

constexpr int      kF        = 4608;
constexpr int      kXJ       = 568;
constexpr uint32_t kStage    = 16384;
constexpr int      kTailN    = 104;
constexpr int      kTailBox  = 52;
constexpr uint32_t kTailBlk  = kTailN * 128;
constexpr uint32_t kPiece    = 8 * 512;
constexpr uint32_t X7        = 0;
constexpr uint32_t XS        = 17 * 1024;
constexpr uint32_t OS        = XS + 9 * kStage;
constexpr uint32_t WS        = OS + 2 * kStage;
constexpr uint32_t X8        = WS + 4 * kPiece;
constexpr uint32_t ZS        = WS + 8 * kPiece;
constexpr uint32_t BARS      = ZS + 768;
constexpr uint32_t FULL      = BARS;
constexpr uint32_t TFULL     = BARS + 72;
constexpr uint32_t EMPTY     = BARS + 144;
constexpr uint32_t WFULL     = BARS + 216;
constexpr uint32_t DONE      = BARS + 224;
constexpr uint32_t ZCHK      = BARS + 232;
constexpr uint32_t XFULL     = BARS + 256;
constexpr uint32_t kSmem     = BARS + 272;
__host__ __device__ constexpr uint32_t tail_off(int i) { return i < 2 ? XS + 7 * kStage + i * kTailBlk : XS + (i - 2) * kTailBlk; }
__host__ __device__ constexpr int tail_stage(int i) { return ((i - 1) * (int)kTailBlk - 1) / (int)kStage; }
__host__ __device__ constexpr int t3_delta(int kb) { return kb < 7 ? 0 : ((int)(kb == 7 ? X7 : X8) - (int)(XS + kb * kStage)) / 16; }
constexpr int kPauseAt = 6, kPauseUntil = 8;
constexpr int kSplit   = 2;
constexpr int kWindow  = 3;
constexpr int kBurst   = 20;

DEV void mbar_init(uint32_t a, uint32_t c) { asm volatile("mbarrier.init.shared::cta.b64 [%0], %1;" :: "r"(a), "r"(c) : "memory"); }
DEV void mbar_expect(uint32_t a, uint32_t tx) { asm volatile("mbarrier.arrive.expect_tx.shared::cta.b64 _, [%0], %1;" :: "r"(a), "r"(tx) : "memory"); }
DEV void mbar_arrive(uint32_t a) { asm volatile("mbarrier.arrive.shared::cta.b64 _, [%0];" :: "r"(a) : "memory"); }
DEV void mbar_wait(uint32_t a, uint32_t par) {
    asm volatile("{\n.reg .pred p;\nL:\nmbarrier.try_wait.parity.shared::cta.b64 p, [%0], %1;\n@!p bra.uni L;\n}"
                 :: "r"(a), "r"(par) : "memory");
}
DEV void mbar_spin(uint32_t a, uint32_t par) {
    asm volatile("{\n.reg .pred p;\nL:\nmbarrier.test_wait.parity.shared::cta.b64 p, [%0], %1;\n@!p bra.uni L;\n}"
                 :: "r"(a), "r"(par) : "memory");
}
DEV bool mbar_try(uint32_t a, uint32_t par) {
    uint32_t ok;
    asm volatile("{\n.reg .pred p;\nmbarrier.try_wait.parity.shared::cta.b64 p, [%1], %2;\nselp.u32 %0, 1, 0, p;\n}"
                 : "=r"(ok) : "r"(a), "r"(par) : "memory");
    return ok;
}
DEV void arrive_cluster_if(uint32_t a, bool p) {
    asm volatile("{\n.reg .pred p;\nsetp.ne.b32 p, %1, 0;\n@p mbarrier.arrive.shared::cluster.b64 _, [%0];\n}"
                 :: "r"(a), "r"((uint32_t)p) : "memory");
}
DEV void tma_ld_w(uint32_t dst, const CUtensorMap* m, int f, int row, uint32_t bar) {
    asm volatile("cp.async.bulk.tensor.3d.shared::cluster.global.mbarrier::complete_tx::bytes [%0], [%1, {0, %3, %4}], [%2];"
                 :: "r"(dst), "l"(m), "r"(bar), "r"(row), "r"(f >> 4) : "memory");
}
DEV void tma_ld_x(uint32_t dst, const CUtensorMap* m, int c0, int c1, uint32_t bar) {
    asm volatile("cp.async.bulk.tensor.2d.shared::cluster.global.mbarrier::complete_tx::bytes.multicast::cluster [%0], [%1, {%3, %4}], [%2], %5;"
                 :: "r"(dst), "l"(m), "r"(bar), "r"(c0), "r"(c1), "h"((uint16_t)3) : "memory");
}
DEV void bulk_ld(uint32_t dst, const void* src, uint32_t bytes, uint32_t bar) {
    asm volatile("cp.async.bulk.shared::cluster.global.mbarrier::complete_tx::bytes [%0], [%1], %2, [%3];"
                 :: "r"(dst), "l"(src), "r"(bytes), "r"(bar) : "memory");
}
DEV void tma_st(const CUtensorMap* m, int c0, int c1, uint32_t src) {
    asm volatile("cp.async.bulk.tensor.2d.global.shared::cta.bulk_group [%0, {%2, %3}], [%1];"
                 :: "l"(m), "r"(src), "r"(c0), "r"(c1) : "memory");
    asm volatile("cp.async.bulk.commit_group;" ::: "memory");
}
DEV void tma_st_wait_read() { asm volatile("cp.async.bulk.wait_group.read 0;" ::: "memory"); }
DEV uint32_t lds32(uint32_t a) { uint32_t v; asm volatile("ld.shared.b32 %0, [%1];" : "=r"(v) : "r"(a)); return v; }
DEV bool elect_one() {
    uint32_t p;
    asm volatile("{\n.reg .pred p;\nelect.sync _|p, 0xffffffff;\nselp.u32 %0, 1, 0, p;\n}" : "=r"(p));
    return p;
}
DEV int fresh_lane() { int v; asm volatile("mov.u32 %0, %%laneid;" : "=r"(v)); return v; }
DEV void prefetch_l2(const void* p) { asm volatile("prefetch.global.L2 [%0];" :: "l"(p)); }
DEV void prefetch_map(const CUtensorMap* m) { asm volatile("prefetch.tensormap [%0];" :: "l"(m) : "memory"); }
DEV void bar_sync(int id) { asm volatile("bar.sync %0, 128;" :: "r"(id) : "memory"); }
template <int ID> DEV void order_wait() { asm volatile("bar.sync %0, 256;" :: "n"(ID) : "memory"); }
template <int ID> DEV void order_signal() { asm volatile("bar.arrive %0, 256;" :: "n"(ID) : "memory"); }
DEV void wg_fence() { asm volatile("wgmma.fence.sync.aligned;" ::: "memory"); }
DEV void wg_commit() { asm volatile("wgmma.commit_group.sync.aligned;" ::: "memory"); }
template <int N> DEV void wg_wait() { asm volatile("wgmma.wait_group.sync.aligned %0;" :: "n"(N) : "memory"); }
DEV uint32_t bf2_add(uint32_t a, uint32_t b) { uint32_t d; asm("add.rn.bf16x2 %0, %1, %2;" : "=r"(d) : "r"(a), "r"(b)); return d; }
DEV uint32_t bf2_sub(uint32_t a, uint32_t b) { uint32_t d; asm("sub.rn.bf16x2 %0, %1, %2;" : "=r"(d) : "r"(a), "r"(b)); return d; }
DEV uint32_t pack_scaled(float lo, float hi, uint32_t spair) {
    uint32_t p;
    asm("cvt.rn.bf16x2.f32 %0, %1, %2;" : "=r"(p) : "f"(hi), "f"(lo));
    asm("mul.rn.bf16x2 %0, %0, %1;" : "+r"(p) : "r"(spair));
    return p;
}
template <int I, int N, typename F>
DEV void static_for(F&& f) {
    if constexpr (I < N) { f(std::integral_constant<int, I>{}); static_for<I + 1, N>(f); }
}

#define ACC8(d, o) "+f"(d[o + 0]), "+f"(d[o + 1]), "+f"(d[o + 2]), "+f"(d[o + 3]), "+f"(d[o + 4]), "+f"(d[o + 5]), "+f"(d[o + 6]), "+f"(d[o + 7])

template <int ACCUM>
DEV void wgmma_n128(float (&d)[64], uint32_t a0, uint32_t a1, uint32_t a2, uint32_t a3, uint64_t desc) {
    asm volatile(
        "wgmma.mma_async.sync.aligned.m64n128k16.f32.bf16.bf16 "
        "{%0,%1,%2,%3,%4,%5,%6,%7,%8,%9,%10,%11,%12,%13,%14,%15,%16,%17,%18,%19,%20,%21,%22,%23,%24,%25,%26,%27,%28,%29,%30,%31,"
        "%32,%33,%34,%35,%36,%37,%38,%39,%40,%41,%42,%43,%44,%45,%46,%47,%48,%49,%50,%51,%52,%53,%54,%55,%56,%57,%58,%59,%60,%61,%62,%63},"
        "{%64,%65,%66,%67}, %68, %69, 1, 1, 0;\n"
        : ACC8(d, 0), ACC8(d, 8), ACC8(d, 16), ACC8(d, 24), ACC8(d, 32), ACC8(d, 40), ACC8(d, 48), ACC8(d, 56)
        : "r"(a0), "r"(a1), "r"(a2), "r"(a3), "l"(desc), "n"(ACCUM));
}
template <int ACCUM>
DEV void wgmma_n104(float (&d)[64], uint32_t a0, uint32_t a1, uint32_t a2, uint32_t a3, uint64_t desc) {
    asm volatile(
        "wgmma.mma_async.sync.aligned.m64n104k16.f32.bf16.bf16 "
        "{%0,%1,%2,%3,%4,%5,%6,%7,%8,%9,%10,%11,%12,%13,%14,%15,%16,%17,%18,%19,%20,%21,%22,%23,%24,%25,%26,%27,%28,%29,%30,%31,"
        "%32,%33,%34,%35,%36,%37,%38,%39,%40,%41,%42,%43,%44,%45,%46,%47,%48,%49,%50,%51},"
        "{%52,%53,%54,%55}, %56, %57, 1, 1, 0;\n"
        : ACC8(d, 0), ACC8(d, 8), ACC8(d, 16), ACC8(d, 24), ACC8(d, 32), ACC8(d, 40),
          "+f"(d[48]), "+f"(d[49]), "+f"(d[50]), "+f"(d[51])
        : "r"(a0), "r"(a1), "r"(a2), "r"(a3), "l"(desc), "n"(ACCUM));
}

template <int KB, bool TAIL>
DEV void mma_block(float (&d)[64], const uint32_t (&a)[144], uint64_t dbase) {
    constexpr uint32_t off = TAIL ? tail_off(KB) : XS + KB * kStage;
    wg_fence();
#pragma unroll
    for (int kk = 0; kk < 4; kk++) {
        const int s = 16 * KB + 4 * kk;
        const uint64_t desc = dbase + (off >> 4) + 2 * kk;
        if (KB == 0 && kk == 0) {
            if (TAIL) wgmma_n104<0>(d, a[s], a[s + 1], a[s + 2], a[s + 3], desc);
            else      wgmma_n128<0>(d, a[s], a[s + 1], a[s + 2], a[s + 3], desc);
        } else {
            if (TAIL) wgmma_n104<1>(d, a[s], a[s + 1], a[s + 2], a[s + 3], desc);
            else      wgmma_n128<1>(d, a[s], a[s + 1], a[s + 2], a[s + 3], desc);
        }
    }
    wg_commit();
}

constexpr uint32_t kMagic = 0x41004280u;
struct DqState {
    uint32_t addr[5];
    uint32_t addr0;
    uint32_t mul[5];
    uint32_t z0, z1;
    uint32_t magic;
    int j;
};

DEV void dq_setup(DqState& q, uint32_t slab, int j, int lane) {
    const int e = (lane & 3) - j;
#pragma unroll
    for (int r = 0; r < 5; r++) {
        const int n = 4 * r + e + 5;
        const int w = (n * 52) >> 8;
        q.addr[r] = slab + (w - 1) * 64 + (lane >> 2) * 8;
        asm("shl.b32 %0, 1, %1;" : "=r"(q.mul[r]) : "r"(25 - 6 * (n - 5 * w)));
    }
    q.addr0 = q.addr[0] - (e < 0 ? 4096 - 512 : 0);
    q.j = j;
    q.magic = kMagic;
}
DEV void dq_zero(DqState& q, uint32_t zpair) {
    q.z0 = bf2_add(__byte_perm(zpair, 0, 0x1010), kMagic);
    q.z1 = bf2_add(__byte_perm(zpair, 0, 0x3232), kMagic);
}
DEV bool zero_exact(uint32_t zpair) {
    const uint32_t z0 = __byte_perm(zpair, 0, 0x1010), z1 = __byte_perm(zpair, 0, 0x3232);
    return bf2_sub(bf2_add(z0, kMagic), kMagic) == bf2_add(z0, 0) && bf2_sub(bf2_add(z1, kMagic), kMagic) == bf2_add(z1, 0);
}
DEV uint32_t dq_pair(uint32_t w, uint32_t mul, uint32_t z, uint32_t magic) {
    uint32_t y;
    asm("mul.lo.u32 %0, %1, %2;" : "=r"(y) : "r"(w), "r"(mul));
    y = __byte_perm(y, 0, 0x3333);
    asm("lop3.b32 %0, %1, 0x0070000E, %2, 0xEA;" : "=r"(y) : "r"(y), "r"(magic));
    return bf2_sub(y, z);
}
template <bool TAIL, int KB>
DEV void dq_load(uint32_t (&a)[144], const DqState& q) {
#pragma unroll
    for (int u = 8 * KB; u < 8 * KB + 8; u++) {
        const int v = u / 5, r = u % 5;
        const uint32_t addr = TAIL ? q.addr[r] + 256 * v
                                   : ((r == 0 && !(v & 1) && v > 0) ? q.addr0 : q.addr[r]) + 4096 * (v >> 1) + 256 * (v & 1);
        asm volatile("ld.shared.v2.b32 {%0, %1}, [%2];" : "=r"(a[2 * u]), "=r"(a[2 * u + 1]) : "r"(addr));
    }
}
template <int SA, int SB>
DEV void dq_conv(uint32_t (&a)[144], const DqState& q) {
#pragma unroll
    for (int u = 2 * SA; u < 2 * SB; u++) {
        uint32_t x0 = dq_pair(a[2 * u], q.mul[u % 5], q.z0, q.magic);
        uint32_t x1 = dq_pair(a[2 * u + 1], q.mul[u % 5], q.z1, q.magic);
        if (u == 0 || u == 71) {
            const int t = fresh_lane() & 3;
            const bool ok = (u == 0) ? (t >= q.j) : (t <= q.j);
            x0 = ok ? x0 : 0u;
            x1 = ok ? x1 : 0u;
        }
        a[2 * u] = x0;
        a[2 * u + 1] = x1;
    }
}

template <typename F>
DEV void stage_out(const float (&d)[64], uint32_t sbase, uint32_t ost, int w, F&& after_wait) {
    const int lane = fresh_lane(), g = lane >> 2, t = lane & 3;
    const uint32_t spair = lds32(sbase + 4 * g);
    const uint32_t o0 = ost + (2 * t) * 128 + (((2 * w + (g >> 2)) ^ (2 * t)) << 4) + 4 * (g & 3);
    const uint32_t o1 = (o0 ^ 16) + 128;
    wg_wait<0>();
    after_wait();
#pragma unroll
    for (int c = 0; c < 16; c++) {
        const uint32_t p0 = pack_scaled(d[4 * c + 0], d[4 * c + 2], spair);
        const uint32_t p1 = pack_scaled(d[4 * c + 1], d[4 * c + 3], spair);
        asm volatile("st.shared.b32 [%0], %1;" :: "r"(o0 + 1024 * c), "r"(p0) : "memory");
        asm volatile("st.shared.b32 [%0], %1;" :: "r"(o1 + 1024 * c), "r"(p1) : "memory");
    }
}
DEV void direct_out(const float (&d)[64], uint32_t sbase, char* out, int col, int cls, int row0, int w) {
    const int lane = fresh_lane(), g = lane >> 2, t = lane & 3;
    const uint32_t spair = lds32(sbase + 4 * g);
    char* p = out + (size_t)(4 * (row0 + 2 * t) + cls) * (2 * kF) + (col + 16 * w + 2 * g) * 2;
    wg_wait<0>();
#pragma unroll
    for (int c = 0; c < kTailN / 8; c++) {
        const uint32_t p0 = pack_scaled(d[4 * c + 0], d[4 * c + 2], spair);
        const uint32_t p1 = pack_scaled(d[4 * c + 1], d[4 * c + 3], spair);
        if (c < kTailN / 8 - 1 || row0 + kTailN <= 512) {
            *(uint32_t*)(p + (size_t)c * (64 * kF)) = p0;
            *(uint32_t*)(p + (size_t)c * (64 * kF) + 8 * kF) = p1;
        }
    }
}

DEV int map_j(int c) { return c >= 64 ? c & 3 : ((c >> 3) & 1) | (((c >> 5) & 1) << 1); }
DEV int drop_bit(int v, int b) { return (v & ((1 << b) - 1)) | ((v >> (b + 1)) << b); }
DEV int map_f(int c) { return c >= 64 ? 16 : drop_bit(drop_bit(c, 5), 3); }
struct Work { int ja, fa, jb, fb, rb; bool tail; };
DEV void tail_work(Work& wk) {
    int b;
    asm volatile("mov.u32 %0, %%ctaid.x;" : "=r"(b));
    const int c = b >> 1, ut = (c * 52) >> 8;
    wk.tail = c < 60;
    wk.jb = ut < 4 ? 2 + (ut & 1) : (ut & 3);
    wk.fb = wk.tail ? (ut < 4 ? 32 + (ut >> 1) : 33 + (ut >> 2)) * 128 + 64 * (b & 1) : 0;
    wk.rb = (c - 5 * ut) * kTailN;
}

struct Ptrs { const uint16_t* x; const uint32_t* w; const uint16_t* s; const uint16_t* z; __nv_bfloat16* out; };
__device__ __noinline__ void fixup(const Ptrs p, int f0, int cls, int row0, int rows) {
    const int f = f0 + (threadIdx.x & 63);
    const uint32_t zr = p.z[f];
    if (zero_exact(zr | (zr << 16))) return;
    const float z = __uint_as_float(zr << 16), s = __uint_as_float((uint32_t)p.s[f] << 16);
    for (int i = row0 + ((threadIdx.x >> 6) & 1); i < row0 + rows && i < 512; i += 2) {
        const int m = 4 * i + cls;
        float acc = 0.f;
        for (int r = 0; r < 57; r++) {
            const uint32_t word = p.w[r * kF + f];
#pragma unroll 1
            for (int e = 0; e < 10; e++) {
                const float dq = __bfloat162float(__float2bfloat16_rn((float)((word >> (3 * e)) & 7) - z));
                const float wv = __bfloat162float(__float2bfloat16_rn(dq * s));
                acc = fmaf(__uint_as_float((uint32_t)p.x[m * 570 + 10 * r + e] << 16), wv, acc);
            }
        }
        p.out[(size_t)m * kF + f] = __float2bfloat16_rn(acc);
    }
}

DEV void consumer(const uint32_t sb, const Work wk, const int wg, const int w, const int lane,
                  const CUtensorMap* om, const Ptrs& ptrs, DqState& q) {
    const uint32_t full = sb + FULL;
    uint32_t rel;
    asm("mapa.shared::cluster.u32 %0, %1, %2;" : "=r"(rel) : "r"(sb + EMPTY), "r"(w & 1));
    const bool do_rel = (lane == 0) && (w < 2);
    const bool storer = (lane == 0) && (w == 3);
    const uint32_t ost = sb + OS + wg * kStage;
    const uint64_t dbase = (uint64_t)((sb & 0x3FFFF) >> 4) | (64ull << 32) | (1ull << 62);
    const uint32_t zs = sb + ZS + 128 * wg + 32 * w;
    const int ocol = wk.ja * kF + wk.fa + wg * 64;

    uint32_t a[144];
    float d[64];

    auto publish = [&](int row) {
        asm volatile("fence.proxy.async.shared::cta;" ::: "memory");
        bar_sync(1 + wg);
        if (storer) tma_st(om, ocol, row, ost);
    };
    auto staging_free = [&]() {
        if (storer) tma_st_wait_read();
        bar_sync(3 + wg);
    };

    const uint32_t sel = 0x3210u + (uint32_t)((size_t)ptrs.out & 1);
    mbar_wait(sb + WFULL, 0);
    dq_zero(q, lds32(zs + (lane & ~3)));
    dq_load<false, 0>(a, q);
    dq_conv<0, 4>(a, q);
    static_for<0, 9>([&](auto kb_) {
        constexpr int kb = decltype(kb_)::value;
        if constexpr (kb == kPauseAt) { if (wg == 1) order_wait<5>(); }
        mbar_spin(full + 8 * kb, 0);
        if constexpr (kb < 8) dq_load<false, kb + 1>(a, q);
        mma_block<kb, false>(d, a, dbase + (1u << 16));
        if constexpr (kb < 8) dq_conv<4 * kb + 4, 4 * kb + 4 + kSplit>(a, q);
        if constexpr (kb == kPauseUntil) { if (wg == 0) order_signal<5>(); }
        if constexpr (kb > 0) { wg_wait<1>(); arrive_cluster_if(rel + 8 * (kb - 1), do_rel); }
        if constexpr (kb < 8) {
            uint32_t c;
            asm volatile("mov.u32 %0, %%clock;" : "=r"(c) :: "memory");
            q.magic = __byte_perm(kMagic, c, sel);
            dq_conv<4 * kb + 4 + kSplit, 4 * kb + 8>(a, q);
        }
    });

    const bool tail = wg == 0 && wk.tail;
#pragma unroll 1
    for (int tile = 1; tile < 4; tile++) {
        stage_out(d, zs + 256, ost, w, [&] { arrive_cluster_if(rel + 8 * 8, do_rel && (tile < 3 || wk.tail)); });
        const bool defer = !(tile == 3 && wk.tail);
        if (!defer) {
            publish(256);
            if (wg == 0) break;
            order_wait<6>();
        }
        const bool rel_lo = do_rel && (tile < 3 || wk.tail), rel_hi = do_rel && tile < 3;
        const bool rel_7 = rel_hi && (tile < 2 || wk.tail);
        static_for<0, 9>([&](auto kb_) {
            constexpr int kb = decltype(kb_)::value;
            if constexpr (kb >= 7) {
                const bool t3 = tile == 3;
                mbar_wait(t3 ? sb + XFULL + 8 * (kb - 7) : full + 8 * kb, t3 ? 0 : tile & 1);
                mma_block<kb, false>(d, a, dbase + ((tile + 1u) << 16) + (t3 ? t3_delta(kb) : 0));
            } else {
                mbar_wait(full + 8 * kb, tile & 1);
                mma_block<kb, false>(d, a, dbase + ((tile + 1u) << 16));
            }
            if constexpr (kb == 0) { if (defer) publish(128 * (tile - 1)); }
            if constexpr (kb == 6) staging_free();
            if constexpr (kb > 0) {
                wg_wait<1>();
                arrive_cluster_if(rel + 8 * (kb - 1), kb - 1 <= tail_stage(8) ? rel_lo : kb == 8 ? rel_7 : rel_hi);
            }
        });
    }
    if (tail) {
        mbar_spin(full, 1);
        static_for<0, 9>([&](auto kb_) {
            constexpr int kb = decltype(kb_)::value;
            mma_block<kb, false>(d, a, dbase + (4u << 16) + (uint64_t)(int64_t)t3_delta(kb));
            if constexpr (kb == 8) order_signal<6>();
            if constexpr (kb < 6) mbar_spin(full + 8 * (kb + 1), 1);
            else if constexpr (kb < 8) mbar_spin(sb + XFULL + 8 * (kb - 6), 0);
            if constexpr (kb == 0) {
                const int l2 = fresh_lane();
                dq_setup(q, sb + WS + w * (57 * 64), wk.jb, l2);
                mbar_spin(sb + WFULL, 1);
                q.z0 = lds32(zs + 512 + (l2 & ~3));
            }
            if constexpr (kb == 6) staging_free();
            if constexpr (kb == 2) dq_zero(q, q.z0);
            if constexpr (kb >= 3) dq_conv<kb - 3, kb - 2>(a, q);
            if constexpr (kb >= 2) dq_load<true, kb - 2>(a, q);
            if constexpr (kb > 0) {
                wg_wait<1>();
                if constexpr (kb - 1 <= tail_stage(8)) arrive_cluster_if(rel + 8 * (kb - 1), do_rel);
            }
        });
    }
    stage_out(d, zs + 256, ost, w, [] {});
    publish(384);

    if (tail) {
        dq_load<true, 7>(a, q);
        dq_load<true, 8>(a, q);
        dq_conv<6, kBurst>(a, q);
        mbar_spin(sb + TFULL, 0);
        static_for<0, 9>([&](auto kb_) {
            constexpr int kb = decltype(kb_)::value;
            mma_block<kb, true>(d, a, dbase + (5u << 16));
            if constexpr (kb < 8) mbar_spin(sb + TFULL + 8 * (kb + 1), 0);
            if constexpr (kBurst + 2 * kb < 36) dq_conv<kBurst + 2 * kb, kBurst + 2 * kb + 2>(a, q);
        });
        if (storer) mbar_arrive(sb + DONE);
        direct_out(d, zs + 640, (char*)ptrs.out, wk.fb, wk.jb, wk.rb, w);
    }
    if (storer) {
        if (!tail) mbar_arrive(sb + DONE);
        tma_st_wait_read();
    }
    mbar_spin(sb + ZCHK, 0);
    if (__builtin_expect(__shfl_sync(0xffffffffu, lds32(sb + ZCHK + 8), 0), 0)) {
        if (storer) asm volatile("cp.async.bulk.wait_group 0;" ::: "memory");
        asm volatile("fence.proxy.async.global;" ::: "memory");
        __threadfence();
        bar_sync(1 + wg);
        fixup(ptrs, wk.fa + 64 * wg, wk.ja, 0, 512);
        if (tail) fixup(ptrs, wk.fb, wk.jb, wk.rb, kTailN);
    }
}

DEV void producer(const uint32_t sb, const Work wk, const int rank, const CUtensorMap* xm, const CUtensorMap* xt,
                  const CUtensorMap* om, const CUtensorMap* wm, const CUtensorMap* wt,
                  const uint32_t* scales2, const uint32_t* zeros2) {
    const int xc = kXJ * wk.ja;
    const uint32_t xdst = sb + rank * (kStage / 2);
#pragma unroll 1
    for (int kb = 1; kb < 9; kb++) {
        if (kb >= kWindow) mbar_wait(sb + FULL + 8 * (kb - kWindow), 0);
        tma_ld_x(xdst + XS + kb * kStage, xm, xc + 64 * kb, 64 * rank, sb + FULL + 8 * kb);
        if (kb < 7) tma_ld_w(sb + WS + (kb + 1) * kPiece, wm, wk.fa, 8 * (kb + 1), sb + FULL + 8 * kb);
        if (kb == 7) bulk_ld(sb + ZS + 256, scales2 + wk.fa / 2, 256, sb + FULL + 8 * 7);
    }
    prefetch_map(om); prefetch_map(xt); prefetch_map(wt);
#pragma unroll 1
    for (int tile = 1; tile < 4; tile++) {
#pragma unroll 1
        for (int kb = 0; kb < (tile == 3 ? 7 : 9); kb++) {
            mbar_wait(sb + EMPTY + 8 * kb, (tile - 1) & 1);
            mbar_expect(sb + FULL + 8 * kb, kStage);
            tma_ld_x(xdst + XS + kb * kStage, xm, xc + 64 * kb, 128 * tile + 64 * rank, sb + FULL + 8 * kb);
            if (tile == 2) {
                if (kb == 0 && wk.tail) {
                    mbar_expect(sb + WFULL, 57 * 256 + 256);
                    tma_ld_w(sb + WS, wt, wk.fb, 0, sb + WFULL);
                    bulk_ld(sb + ZS + 512, zeros2 + wk.fb / 2, 128, sb + WFULL);
                    bulk_ld(sb + ZS + 640, scales2 + wk.fb / 2, 128, sb + WFULL);
                }
                if (kb == 2 || kb == 5) {
                    const int e = kb == 5;
                    mbar_expect(sb + XFULL + 8 * e, kStage);
                    tma_ld_x(xdst + (e ? X8 : X7), xm, xc + 64 * (7 + e), 384 + 64 * rank, sb + XFULL + 8 * e);
                }
            }
        }
    }
    if (wk.tail) {
        const int tc = kXJ * wk.jb, tr = wk.rb + (kTailN - kTailBox) * rank;
        const uint32_t tdst = sb + rank * ((kTailN - kTailBox) * 128);
#pragma unroll 1
        for (int kb = 0; kb < 9; kb++) {
            if (kb < 2) mbar_wait(sb + EMPTY + 8 * (7 + kb), 0);
            else mbar_wait(sb + EMPTY + 8 * tail_stage(kb), 1);
            mbar_expect(sb + TFULL + 8 * kb, 2 * kTailBox * 128);
            tma_ld_x(tdst + tail_off(kb), xt, tc + 64 * kb, tr, sb + TFULL + 8 * kb);
        }
    }
}

__global__ void __cluster_dims__(2, 1, 1) __launch_bounds__(384, 1)
gptq_kernel(const __grid_constant__ CUtensorMap xm, const __grid_constant__ CUtensorMap xt,
            const __grid_constant__ CUtensorMap om, const __grid_constant__ CUtensorMap wm,
            const __grid_constant__ CUtensorMap wt,
            const uint32_t* __restrict__ scales2, const uint32_t* __restrict__ zeros2,
            const char* __restrict__ xg, const char* __restrict__ wg_ptr, char* __restrict__ outp) {
    extern __shared__ __align__(1024) uint8_t smem[];
    const uint32_t sb = (uint32_t)__cvta_generic_to_shared(smem);
    if ((threadIdx.x >> 5) == 4) {
        const int ci = map_f(blockIdx.x >> 1) * 2 + (blockIdx.x & 1), j = map_j(blockIdx.x >> 1), l = threadIdx.x & 31;
        const int off = l < 16 ? (j + 4 * (l >> 2)) * (4 * kF) + ci * 512 + (l & 3) * 128
                               : (4 * (ci & 31) + (l & 3)) * 4560 + 1136 * j + ((l >> 2) - 4) * 128;
        prefetch_l2((l < 16 ? wg_ptr : xg) + off);
        prefetch_map(&wm);
        prefetch_map(&xm);
    }
    const int warp = __shfl_sync(0xffffffffu, threadIdx.x >> 5, 0);
    const int lane = threadIdx.x & 31;
    const int rank = blockIdx.x & 1, c = blockIdx.x >> 1;
    Work wk;
    wk.ja = map_j(c);
    wk.fa = (map_f(c) * 2 + rank) * 128;

    if ((warp >= 9 || warp < 3) && elect_one()) {
        if (warp < 3) {
            mbar_init(sb + WFULL + 8 * warp, warp == 1 ? 2 : 1);
            if (warp > 0) mbar_init(sb + XFULL - 8 + 8 * warp, 1);
        } else {
            const uint32_t b = sb + BARS + 72 * (warp - 9), cnt = warp == 11 ? 4 : 1;
#pragma unroll
            for (int i = 0; i < 9; i++) mbar_init(b + 8 * i, cnt);
        }
        asm volatile("fence.mbarrier_init.release.cluster;" ::: "memory");
    }
    __syncwarp();
    asm volatile("barrier.cluster.arrive.relaxed.aligned;" ::: "memory");
    if (warp == 0 && elect_one()) {
        tma_ld_w(sb + WS, &wm, wk.fa, 0, sb + WFULL);
        bulk_ld(sb + ZS, zeros2 + wk.fa / 2, 256, sb + WFULL);
        mbar_expect(sb + WFULL, kPiece + 256);
    }
    __syncwarp();
    asm volatile("barrier.cluster.wait.aligned;" ::: "memory");
    if (warp == 8 && elect_one()) {
        tma_ld_x(sb + XS + rank * (kStage / 2), &xm, kXJ * wk.ja, 64 * rank, sb + FULL);
        tma_ld_w(sb + WS + kPiece, &wm, wk.fa, 8, sb + FULL);
    }
    if (warp == 10 && elect_one()) {
#pragma unroll
        for (int i = 0; i < 9; i++) mbar_expect(sb + FULL + 8 * i, kStage + (i < 7 ? kPiece : i == 7 ? 256 : 0));
    }
    __syncwarp();

    if (warp >= 8) {
        asm volatile("setmaxnreg.dec.sync.aligned.u32 24;");
        if (warp == 11) {
            tail_work(wk);
            mbar_wait(sb + FULL + 8 * 3, 0);
            const bool ok = zero_exact(__ldg(zeros2 + wk.fa / 2 + lane)) && zero_exact(__ldg(zeros2 + wk.fa / 2 + 32 + lane)) &&
                            zero_exact(__ldg(zeros2 + wk.fb / 2 + lane));
            const uint32_t bad = !__all_sync(0xffffffffu, ok);
            if (lane == 0) {
                asm volatile("st.shared.b32 [%0], %1;" :: "r"(sb + ZCHK + 8), "r"(bad) : "memory");
                mbar_arrive(sb + ZCHK);
            }
        }
        if (!elect_one()) return;
        if (warp == 8) {
            tail_work(wk);
            producer(sb, wk, rank, &xm, &xt, &om, &wm, &wt, scales2, zeros2);
        } else if (warp == 9) {
            int n = 0;
            while (!mbar_try(sb + DONE, 0)) { if (++n > (1 << 20)) __trap(); }
        }
    } else {
        tail_work(wk);
        asm volatile("setmaxnreg.inc.sync.aligned.u32 240;");
        DqState q;
        dq_setup(q, sb + WS + warp * 512, wk.ja, lane);
        asm volatile("{\n.reg .pred p;\nsetp.ne.b32 p, %0, 0;\n@p st.shared.v4.b32 [%1], {%2, %3, %4, %5};\n@p st.shared.v4.b32 [%6], {%7, %8, %9, %10};\n}"
                     :: "r"((uint32_t)((size_t)outp & 1)), "r"(q.addr[0]), "r"(q.addr[1]), "r"(q.addr[2]), "r"(q.addr[3]), "r"(q.mul[0]),
                        "r"(q.addr[4]), "r"(q.mul[1]), "r"(q.mul[2]), "r"(q.mul[3]), "r"(q.mul[4]));
        const Ptrs ptrs{(const uint16_t*)xg, (const uint32_t*)wg_ptr, (const uint16_t*)scales2, (const uint16_t*)zeros2, (__nv_bfloat16*)outp};
        consumer(sb, wk, warp >> 2, warp & 3, lane, &om, ptrs, q);
    }
}

typedef CUresult (*EncodeFn)(CUtensorMap*, CUtensorMapDataType, cuuint32_t, void*, const cuuint64_t*, const cuuint64_t*,
                             const cuuint32_t*, const cuuint32_t*, CUtensorMapInterleave, CUtensorMapSwizzle,
                             CUtensorMapL2promotion, CUtensorMapFloatOOBfill);

void make_map(EncodeFn enc, CUtensorMap* m, const void* p, uint64_t cols, uint32_t rows, CUtensorMapL2promotion promo) {
    cuuint64_t gd[2] = {cols, 512}, gs[1] = {2 * cols};
    cuuint32_t bx[2] = {64, rows}, es[2] = {1, 1};
    enc(m, CU_TENSOR_MAP_DATA_TYPE_BFLOAT16, 2, const_cast<void*>(p), gd, gs, bx, es, CU_TENSOR_MAP_INTERLEAVE_NONE,
        CU_TENSOR_MAP_SWIZZLE_128B, promo, CU_TENSOR_MAP_FLOAT_OOB_FILL_NONE);
}
void make_wmap(EncodeFn enc, CUtensorMap* m, const void* p, uint32_t rows, uint32_t groups) {
    cuuint64_t gd[3] = {16, 57, 288}, gs[2] = {4 * kF, 64};
    cuuint32_t bx[3] = {16, rows, groups}, es[3] = {1, 1, 1};
    enc(m, CU_TENSOR_MAP_DATA_TYPE_INT32, 3, const_cast<void*>(p), gd, gs, bx, es, CU_TENSOR_MAP_INTERLEAVE_NONE,
        CU_TENSOR_MAP_SWIZZLE_NONE, CU_TENSOR_MAP_L2_PROMOTION_L2_128B, CU_TENSOR_MAP_FLOAT_OOB_FILL_NONE);
}

}

extern "C" void kernel_launch(void* const* d_in, const int* in_sizes, int n_in, void* d_out, int out_size) {
    static EncodeFn enc = nullptr;
    if (!enc) {
        void* fn = nullptr;
        cudaDriverEntryPointQueryResult qr;
        cudaGetDriverEntryPoint("cuTensorMapEncodeTiled", &fn, cudaEnableDefault, &qr);
        enc = (EncodeFn)fn;
        cudaFuncSetAttribute(gptq_kernel, cudaFuncAttributeMaxDynamicSharedMemorySize, kSmem);
    }
    CUtensorMap xm, xt, om, wm, wt;
    make_map(enc, &xm, d_in[0], 4 * 570, 64, CU_TENSOR_MAP_L2_PROMOTION_L2_128B);
    make_map(enc, &xt, d_in[0], 4 * 570, kTailBox, CU_TENSOR_MAP_L2_PROMOTION_L2_128B);
    make_map(enc, &om, d_out, 4 * kF, 128, CU_TENSOR_MAP_L2_PROMOTION_NONE);
    make_wmap(enc, &wm, d_in[1], 8, 8);
    make_wmap(enc, &wt, d_in[1], 57, 4);
    gptq_kernel<<<132, 384, kSmem, cudaStreamPerThread>>>(xm, xt, om, wm, wt, (const uint32_t*)d_in[2], (const uint32_t*)d_in[3],
                                                       (const char*)d_in[0], (const char*)d_in[1], (char*)d_out);
}
```

```cpp
#include <cuda_runtime.h>
#include <cuda_bf16.h>
#include <cuda.h>
#include <stdint.h>
#include <type_traits>

#define DEV __device__ __forceinline__

namespace {

constexpr int      kF        = 4608;
constexpr int      kXJ       = 568;
constexpr uint32_t kStage    = 16384;
constexpr int      kTailN    = 104;
constexpr int      kTailBox  = 52;
constexpr uint32_t kTailBlk  = kTailN * 128;
constexpr uint32_t kPiece    = 8 * 512;
constexpr uint32_t X7        = 0;
constexpr uint32_t XS        = 17 * 1024;
constexpr uint32_t OS        = XS + 9 * kStage;
constexpr uint32_t WS        = OS + 2 * kStage;
constexpr uint32_t X8        = WS + 4 * kPiece;
constexpr uint32_t ZS        = WS + 8 * kPiece;
constexpr uint32_t BARS      = ZS + 768;
constexpr uint32_t FULL      = BARS;
constexpr uint32_t TFULL     = BARS + 72;
constexpr uint32_t EMPTY     = BARS + 144;
constexpr uint32_t WFULL     = BARS + 216;
constexpr uint32_t DONE      = BARS + 224;
constexpr uint32_t ZCHK      = BARS + 232;
constexpr uint32_t XFULL     = BARS + 256;
constexpr uint32_t kSmem     = BARS + 272;
__host__ __device__ constexpr uint32_t tail_off(int i) { return i < 2 ? XS + 7 * kStage + i * kTailBlk : XS + (i - 2) * kTailBlk; }
__host__ __device__ constexpr int tail_stage(int i) { return ((i - 1) * (int)kTailBlk - 1) / (int)kStage; }
__host__ __device__ constexpr int t3_delta(int kb) { return kb < 7 ? 0 : ((int)(kb == 7 ? X7 : X8) - (int)(XS + kb * kStage)) / 16; }
constexpr int kPauseAt = 6, kPauseUntil = 8;
constexpr int kSplit   = 2;
constexpr int kWindow  = 3;
constexpr int kBurst   = 20;

DEV void mbar_init(uint32_t a, uint32_t c) { asm volatile("mbarrier.init.shared::cta.b64 [%0], %1;" :: "r"(a), "r"(c) : "memory"); }
DEV void mbar_expect(uint32_t a, uint32_t tx) { asm volatile("mbarrier.arrive.expect_tx.shared::cta.b64 _, [%0], %1;" :: "r"(a), "r"(tx) : "memory"); }
DEV void mbar_arrive(uint32_t a) { asm volatile("mbarrier.arrive.shared::cta.b64 _, [%0];" :: "r"(a) : "memory"); }
DEV void mbar_wait(uint32_t a, uint32_t par) {
    asm volatile("{\n.reg .pred p;\nL:\nmbarrier.try_wait.parity.shared::cta.b64 p, [%0], %1;\n@!p bra.uni L;\n}"
                 :: "r"(a), "r"(par) : "memory");
}
DEV void mbar_spin(uint32_t a, uint32_t par) {
    asm volatile("{\n.reg .pred p;\nL:\nmbarrier.test_wait.parity.shared::cta.b64 p, [%0], %1;\n@!p bra.uni L;\n}"
                 :: "r"(a), "r"(par) : "memory");
}
DEV bool mbar_try(uint32_t a, uint32_t par) {
    uint32_t ok;
    asm volatile("{\n.reg .pred p;\nmbarrier.try_wait.parity.shared::cta.b64 p, [%1], %2;\nselp.u32 %0, 1, 0, p;\n}"
                 : "=r"(ok) : "r"(a), "r"(par) : "memory");
    return ok;
}
DEV void arrive_cluster_if(uint32_t a, bool p) {
    asm volatile("{\n.reg .pred p;\nsetp.ne.b32 p, %1, 0;\n@p mbarrier.arrive.shared::cluster.b64 _, [%0];\n}"
                 :: "r"(a), "r"((uint32_t)p) : "memory");
}
DEV void tma_ld_w(uint32_t dst, const CUtensorMap* m, int f, int row, uint32_t bar) {
    asm volatile("cp.async.bulk.tensor.3d.shared::cluster.global.mbarrier::complete_tx::bytes [%0], [%1, {0, %3, %4}], [%2];"
                 :: "r"(dst), "l"(m), "r"(bar), "r"(row), "r"(f >> 4) : "memory");
}
DEV void tma_ld_x(uint32_t dst, const CUtensorMap* m, int c0, int c1, uint32_t bar) {
    asm volatile("cp.async.bulk.tensor.2d.shared::cluster.global.mbarrier::complete_tx::bytes.multicast::cluster [%0], [%1, {%3, %4}], [%2], %5;"
                 :: "r"(dst), "l"(m), "r"(bar), "r"(c0), "r"(c1), "h"((uint16_t)3) : "memory");
}
DEV void bulk_ld(uint32_t dst, const void* src, uint32_t bytes, uint32_t bar) {
    asm volatile("cp.async.bulk.shared::cluster.global.mbarrier::complete_tx::bytes [%0], [%1], %2, [%3];"
                 :: "r"(dst), "l"(src), "r"(bytes), "r"(bar) : "memory");
}
DEV void tma_st(const CUtensorMap* m, int c0, int c1, uint32_t src) {
    asm volatile("cp.async.bulk.tensor.2d.global.shared::cta.bulk_group [%0, {%2, %3}], [%1];"
                 :: "l"(m), "r"(src), "r"(c0), "r"(c1) : "memory");
    asm volatile("cp.async.bulk.commit_group;" ::: "memory");
}
DEV void tma_st_wait_read() { asm volatile("cp.async.bulk.wait_group.read 0;" ::: "memory"); }
DEV uint32_t lds32(uint32_t a) { uint32_t v; asm volatile("ld.shared.b32 %0, [%1];" : "=r"(v) : "r"(a)); return v; }
DEV bool elect_one() {
    uint32_t p;
    asm volatile("{\n.reg .pred p;\nelect.sync _|p, 0xffffffff;\nselp.u32 %0, 1, 0, p;\n}" : "=r"(p));
    return p;
}
DEV int fresh_lane() { int v; asm volatile("mov.u32 %0, %%laneid;" : "=r"(v)); return v; }
DEV void prefetch_l2(const void* p) { asm volatile("prefetch.global.L2 [%0];" :: "l"(p)); }
DEV void prefetch_map(const CUtensorMap* m) { asm volatile("prefetch.tensormap [%0];" :: "l"(m) : "memory"); }
DEV void bar_sync(int id) { asm volatile("bar.sync %0, 128;" :: "r"(id) : "memory"); }
template <int ID> DEV void order_wait() { asm volatile("bar.sync %0, 256;" :: "n"(ID) : "memory"); }
template <int ID> DEV void order_signal() { asm volatile("bar.arrive %0, 256;" :: "n"(ID) : "memory"); }
DEV void wg_fence() { asm volatile("wgmma.fence.sync.aligned;" ::: "memory"); }
DEV void wg_commit() { asm volatile("wgmma.commit_group.sync.aligned;" ::: "memory"); }
template <int N> DEV void wg_wait() { asm volatile("wgmma.wait_group.sync.aligned %0;" :: "n"(N) : "memory"); }
DEV uint32_t bf2_add(uint32_t a, uint32_t b) { uint32_t d; asm("add.rn.bf16x2 %0, %1, %2;" : "=r"(d) : "r"(a), "r"(b)); return d; }
DEV uint32_t bf2_sub(uint32_t a, uint32_t b) { uint32_t d; asm("sub.rn.bf16x2 %0, %1, %2;" : "=r"(d) : "r"(a), "r"(b)); return d; }
DEV uint32_t pack_scaled(float lo, float hi, uint32_t spair) {
    uint32_t p;
    asm("cvt.rn.bf16x2.f32 %0, %1, %2;" : "=r"(p) : "f"(hi), "f"(lo));
    asm("mul.rn.bf16x2 %0, %0, %1;" : "+r"(p) : "r"(spair));
    return p;
}
template <int I, int N, typename F>
DEV void static_for(F&& f) {
    if constexpr (I < N) { f(std::integral_constant<int, I>{}); static_for<I + 1, N>(f); }
}

#define ACC8(d, o) "+f"(d[o + 0]), "+f"(d[o + 1]), "+f"(d[o + 2]), "+f"(d[o + 3]), "+f"(d[o + 4]), "+f"(d[o + 5]), "+f"(d[o + 6]), "+f"(d[o + 7])

template <int ACCUM>
DEV void wgmma_n128(float (&d)[64], uint32_t a0, uint32_t a1, uint32_t a2, uint32_t a3, uint64_t desc) {
    asm volatile(
        "wgmma.mma_async.sync.aligned.m64n128k16.f32.bf16.bf16 "
        "{%0,%1,%2,%3,%4,%5,%6,%7,%8,%9,%10,%11,%12,%13,%14,%15,%16,%17,%18,%19,%20,%21,%22,%23,%24,%25,%26,%27,%28,%29,%30,%31,"
        "%32,%33,%34,%35,%36,%37,%38,%39,%40,%41,%42,%43,%44,%45,%46,%47,%48,%49,%50,%51,%52,%53,%54,%55,%56,%57,%58,%59,%60,%61,%62,%63},"
        "{%64,%65,%66,%67}, %68, %69, 1, 1, 0;\n"
        : ACC8(d, 0), ACC8(d, 8), ACC8(d, 16), ACC8(d, 24), ACC8(d, 32), ACC8(d, 40), ACC8(d, 48), ACC8(d, 56)
        : "r"(a0), "r"(a1), "r"(a2), "r"(a3), "l"(desc), "n"(ACCUM));
}
template <int ACCUM>
DEV void wgmma_n104(float (&d)[64], uint32_t a0, uint32_t a1, uint32_t a2, uint32_t a3, uint64_t desc) {
    asm volatile(
        "wgmma.mma_async.sync.aligned.m64n104k16.f32.bf16.bf16 "
        "{%0,%1,%2,%3,%4,%5,%6,%7,%8,%9,%10,%11,%12,%13,%14,%15,%16,%17,%18,%19,%20,%21,%22,%23,%24,%25,%26,%27,%28,%29,%30,%31,"
        "%32,%33,%34,%35,%36,%37,%38,%39,%40,%41,%42,%43,%44,%45,%46,%47,%48,%49,%50,%51},"
        "{%52,%53,%54,%55}, %56, %57, 1, 1, 0;\n"
        : ACC8(d, 0), ACC8(d, 8), ACC8(d, 16), ACC8(d, 24), ACC8(d, 32), ACC8(d, 40),
          "+f"(d[48]), "+f"(d[49]), "+f"(d[50]), "+f"(d[51])
        : "r"(a0), "r"(a1), "r"(a2), "r"(a3), "l"(desc), "n"(ACCUM));
}

template <int KB, bool TAIL>
DEV void mma_block(float (&d)[64], const uint32_t (&a)[144], uint64_t dbase) {
    constexpr uint32_t off = TAIL ? tail_off(KB) : XS + KB * kStage;
    wg_fence();
#pragma unroll
    for (int kk = 0; kk < 4; kk++) {
        const int s = 16 * KB + 4 * kk;
        const uint64_t desc = dbase + (off >> 4) + 2 * kk;
        if (KB == 0 && kk == 0) {
            if (TAIL) wgmma_n104<0>(d, a[s], a[s + 1], a[s + 2], a[s + 3], desc);
            else      wgmma_n128<0>(d, a[s], a[s + 1], a[s + 2], a[s + 3], desc);
        } else {
            if (TAIL) wgmma_n104<1>(d, a[s], a[s + 1], a[s + 2], a[s + 3], desc);
            else      wgmma_n128<1>(d, a[s], a[s + 1], a[s + 2], a[s + 3], desc);
        }
    }
    wg_commit();
}

constexpr uint32_t kMagic = 0x41004280u;
struct DqState {
    uint32_t addr[5];
    uint32_t addr0;
    uint32_t mul[5];
    uint32_t z0, z1;
    uint32_t magic;
    int j;
};

DEV void dq_setup(DqState& q, uint32_t slab, int j, int lane) {
    const int e = (lane & 3) - j;
#pragma unroll
    for (int r = 0; r < 5; r++) {
        const int n = 4 * r + e + 5;
        const int w = (n * 52) >> 8;
        q.addr[r] = slab + (w - 1) * 64 + (lane >> 2) * 8;
        asm("shl.b32 %0, 1, %1;" : "=r"(q.mul[r]) : "r"(25 - 6 * (n - 5 * w)));
    }
    q.addr0 = q.addr[0] - (e < 0 ? 4096 - 512 : 0);
    q.j = j;
    q.magic = kMagic;
}
DEV void dq_zero(DqState& q, uint32_t zpair) {
    q.z0 = bf2_add(__byte_perm(zpair, 0, 0x1010), kMagic);
    q.z1 = bf2_add(__byte_perm(zpair, 0, 0x3232), kMagic);
}
DEV bool zero_exact(uint32_t zpair) {
    const uint32_t z0 = __byte_perm(zpair, 0, 0x1010), z1 = __byte_perm(zpair, 0, 0x3232);
    return bf2_sub(bf2_add(z0, kMagic), kMagic) == bf2_add(z0, 0) && bf2_sub(bf2_add(z1, kMagic), kMagic) == bf2_add(z1, 0);
}
DEV uint32_t dq_pair(uint32_t w, uint32_t mul, uint32_t z, uint32_t magic) {
    uint32_t y;
    asm("mul.lo.u32 %0, %1, %2;" : "=r"(y) : "r"(w), "r"(mul));
    y = __byte_perm(y, 0, 0x3333);
    asm("lop3.b32 %0, %1, 0x0070000E, %2, 0xEA;" : "=r"(y) : "r"(y), "r"(magic));
    return bf2_sub(y, z);
}
template <bool TAIL, int KB>
DEV void dq_load(uint32_t (&a)[144], const DqState& q) {
#pragma unroll
    for (int u = 8 * KB; u < 8 * KB + 8; u++) {
        const int v = u / 5, r = u % 5;
        const uint32_t addr = TAIL ? q.addr[r] + 256 * v
                                   : ((r == 0 && !(v & 1) && v > 0) ? q.addr0 : q.addr[r]) + 4096 * (v >> 1) + 256 * (v & 1);
        asm volatile("ld.shared.v2.b32 {%0, %1}, [%2];" : "=r"(a[2 * u]), "=r"(a[2 * u + 1]) : "r"(addr));
    }
}
template <int SA, int SB>
DEV void dq_conv(uint32_t (&a)[144], const DqState& q) {
#pragma unroll
    for (int u = 2 * SA; u < 2 * SB; u++) {
        uint32_t x0 = dq_pair(a[2 * u], q.mul[u % 5], q.z0, q.magic);
        uint32_t x1 = dq_pair(a[2 * u + 1], q.mul[u % 5], q.z1, q.magic);
        if (u == 0 || u == 71) {
            const int t = fresh_lane() & 3;
            const bool ok = (u == 0) ? (t >= q.j) : (t <= q.j);
            x0 = ok ? x0 : 0u;
            x1 = ok ? x1 : 0u;
        }
        a[2 * u] = x0;
        a[2 * u + 1] = x1;
    }
}

template <typename F>
DEV void stage_out(const float (&d)[64], uint32_t sbase, uint32_t ost, int w, F&& after_wait) {
    const int lane = fresh_lane(), g = lane >> 2, t = lane & 3;
    const uint32_t spair = lds32(sbase + 4 * g);
    const uint32_t o0 = ost + (2 * t) * 128 + (((2 * w + (g >> 2)) ^ (2 * t)) << 4) + 4 * (g & 3);
    const uint32_t o1 = (o0 ^ 16) + 128;
    wg_wait<0>();
    after_wait();
#pragma unroll
    for (int c = 0; c < 16; c++) {
        const uint32_t p0 = pack_scaled(d[4 * c + 0], d[4 * c + 2], spair);
        const uint32_t p1 = pack_scaled(d[4 * c + 1], d[4 * c + 3], spair);
        asm volatile("st.shared.b32 [%0], %1;" :: "r"(o0 + 1024 * c), "r"(p0) : "memory");
        asm volatile("st.shared.b32 [%0], %1;" :: "r"(o1 + 1024 * c), "r"(p1) : "memory");
    }
}
DEV void direct_out(const float (&d)[64], uint32_t sbase, char* out, int col, int cls, int row0, int w) {
    const int lane = fresh_lane(), g = lane >> 2, t = lane & 3;
    const uint32_t spair = lds32(sbase + 4 * g);
    char* p = out + (size_t)(4 * (row0 + 2 * t) + cls) * (2 * kF) + (col + 16 * w + 2 * g) * 2;
    wg_wait<0>();
#pragma unroll
    for (int c = 0; c < kTailN / 8; c++) {
        const uint32_t p0 = pack_scaled(d[4 * c + 0], d[4 * c + 2], spair);
        const uint32_t p1 = pack_scaled(d[4 * c + 1], d[4 * c + 3], spair);
        if (c < kTailN / 8 - 1 || row0 + kTailN <= 512) {
            *(uint32_t*)(p + (size_t)c * (64 * kF)) = p0;
            *(uint32_t*)(p + (size_t)c * (64 * kF) + 8 * kF) = p1;
        }
    }
}

DEV int map_j(int c) { return c >= 64 ? c & 3 : ((c >> 3) & 1) | (((c >> 5) & 1) << 1); }
DEV int drop_bit(int v, int b) { return (v & ((1 << b) - 1)) | ((v >> (b + 1)) << b); }
DEV int map_f(int c) { return c >= 64 ? 16 : drop_bit(drop_bit(c, 5), 3); }
struct Work { int ja, fa, jb, fb, rb; bool tail; };
DEV void tail_work(Work& wk) {
    int b;
    asm volatile("mov.u32 %0, %%ctaid.x;" : "=r"(b));
    const int c = b >> 1, ut = (c * 52) >> 8;
    wk.tail = c < 60;
    wk.jb = ut < 4 ? 2 + (ut & 1) : (ut & 3);
    wk.fb = wk.tail ? (ut < 4 ? 32 + (ut >> 1) : 33 + (ut >> 2)) * 128 + 64 * (b & 1) : 0;
    wk.rb = (c - 5 * ut) * kTailN;
}

struct Ptrs { const uint16_t* x; const uint32_t* w; const uint16_t* s; const uint16_t* z; __nv_bfloat16* out; };
__device__ __noinline__ void fixup(const Ptrs p, int f0, int cls, int row0, int rows) {
    const int f = f0 + (threadIdx.x & 63);
    const uint32_t zr = p.z[f];
    if (zero_exact(zr | (zr << 16))) return;
    const float z = __uint_as_float(zr << 16), s = __uint_as_float((uint32_t)p.s[f] << 16);
    for (int i = row0 + ((threadIdx.x >> 6) & 1); i < row0 + rows && i < 512; i += 2) {
        const int m = 4 * i + cls;
        float acc = 0.f;
        for (int r = 0; r < 57; r++) {
            const uint32_t word = p.w[r * kF + f];
#pragma unroll 1
            for (int e = 0; e < 10; e++) {
                const float dq = __bfloat162float(__float2bfloat16_rn((float)((word >> (3 * e)) & 7) - z));
                const float wv = __bfloat162float(__float2bfloat16_rn(dq * s));
                acc = fmaf(__uint_as_float((uint32_t)p.x[m * 570 + 10 * r + e] << 16), wv, acc);
            }
        }
        p.out[(size_t)m * kF + f] = __float2bfloat16_rn(acc);
    }
}

DEV void consumer(const uint32_t sb, const Work wk, const int wg, const int w, const int lane,
                  const CUtensorMap* om, const Ptrs& ptrs, DqState& q) {
    const uint32_t full = sb + FULL;
    uint32_t rel;
    asm("mapa.shared::cluster.u32 %0, %1, %2;" : "=r"(rel) : "r"(sb + EMPTY), "r"(w & 1));
    const bool do_rel = (lane == 0) && (w < 2);
    const bool storer = (lane == 0) && (w == 3);
    const uint32_t ost = sb + OS + wg * kStage;
    const uint64_t dbase = (uint64_t)((sb & 0x3FFFF) >> 4) | (64ull << 32) | (1ull << 62);
    const uint32_t zs = sb + ZS + 128 * wg + 32 * w;
    const int ocol = wk.ja * kF + wk.fa + wg * 64;

    uint32_t a[144];
    float d[64];

    auto publish = [&](int row) {
        asm volatile("fence.proxy.async.shared::cta;" ::: "memory");
        bar_sync(1 + wg);
        if (storer) tma_st(om, ocol, row, ost);
    };
    auto staging_free = [&]() {
        if (storer) tma_st_wait_read();
        bar_sync(3 + wg);
    };

    const uint32_t sel = 0x3210u + (uint32_t)((size_t)ptrs.out & 1);
    mbar_wait(sb + WFULL, 0);
    dq_zero(q, lds32(zs + (lane & ~3)));
    dq_load<false, 0>(a, q);
    dq_conv<0, 4>(a, q);
    static_for<0, 9>([&](auto kb_) {
        constexpr int kb = decltype(kb_)::value;
        if constexpr (kb == kPauseAt) { if (wg == 1) order_wait<5>(); }
        mbar_spin(full + 8 * kb, 0);
        if constexpr (kb < 8) dq_load<false, kb + 1>(a, q);
        mma_block<kb, false>(d, a, dbase + (1u << 16));
        if constexpr (kb < 8) dq_conv<4 * kb + 4, 4 * kb + 4 + kSplit>(a, q);
        if constexpr (kb == kPauseUntil) { if (wg == 0) order_signal<5>(); }
        if constexpr (kb > 0) { wg_wait<1>(); arrive_cluster_if(rel + 8 * (kb - 1), do_rel); }
        if constexpr (kb < 8) {
            uint32_t c;
            asm volatile("mov.u32 %0, %%clock;" : "=r"(c) :: "memory");
            q.magic = __byte_perm(kMagic, c, sel);
            dq_conv<4 * kb + 4 + kSplit, 4 * kb + 8>(a, q);
        }
    });

    const bool tail = wg == 0 && wk.tail;
#pragma unroll 1
    for (int tile = 1; tile < 4; tile++) {
        stage_out(d, zs + 256, ost, w, [&] { arrive_cluster_if(rel + 8 * 8, do_rel && (tile < 3 || wk.tail)); });
        const bool defer = !(tile == 3 && wk.tail);
        if (!defer) {
            publish(256);
            if (wg == 0) break;
            order_wait<6>();
        }
        const bool rel_lo = do_rel && (tile < 3 || wk.tail), rel_hi = do_rel && tile < 3;
        const bool rel_7 = rel_hi && (tile < 2 || wk.tail);
        static_for<0, 9>([&](auto kb_) {
            constexpr int kb = decltype(kb_)::value;
            if constexpr (kb >= 7) {
                const bool t3 = tile == 3;
                mbar_wait(t3 ? sb + XFULL + 8 * (kb - 7) : full + 8 * kb, t3 ? 0 : tile & 1);
                mma_block<kb, false>(d, a, dbase + ((tile + 1u) << 16) + (t3 ? t3_delta(kb) : 0));
            } else {
                mbar_wait(full + 8 * kb, tile & 1);
                mma_block<kb, false>(d, a, dbase + ((tile + 1u) << 16));
            }
            if constexpr (kb == 0) { if (defer) publish(128 * (tile - 1)); }
            if constexpr (kb == 6) staging_free();
            if constexpr (kb > 0) {
                wg_wait<1>();
                arrive_cluster_if(rel + 8 * (kb - 1), kb - 1 <= tail_stage(8) ? rel_lo : kb == 8 ? rel_7 : rel_hi);
            }
        });
    }
    if (tail) {
        mbar_spin(full, 1);
        static_for<0, 9>([&](auto kb_) {
            constexpr int kb = decltype(kb_)::value;
            mma_block<kb, false>(d, a, dbase + (4u << 16) + (uint64_t)(int64_t)t3_delta(kb));
            if constexpr (kb == 8) order_signal<6>();
            if constexpr (kb < 6) mbar_spin(full + 8 * (kb + 1), 1);
            else if constexpr (kb < 8) mbar_spin(sb + XFULL + 8 * (kb - 6), 0);
            if constexpr (kb == 0) {
                const int l2 = fresh_lane();
                dq_setup(q, sb + WS + w * (57 * 64), wk.jb, l2);
                mbar_spin(sb + WFULL, 1);
                q.z0 = lds32(zs + 512 + (l2 & ~3));
            }
            if constexpr (kb == 6) staging_free();
            if constexpr (kb == 2) dq_zero(q, q.z0);
            if constexpr (kb >= 3) dq_conv<kb - 3, kb - 2>(a, q);
            if constexpr (kb >= 2) dq_load<true, kb - 2>(a, q);
            if constexpr (kb > 0) {
                wg_wait<1>();
                if constexpr (kb - 1 <= tail_stage(8)) arrive_cluster_if(rel + 8 * (kb - 1), do_rel);
            }
        });
    }
    stage_out(d, zs + 256, ost, w, [] {});
    publish(384);

    if (tail) {
        dq_load<true, 7>(a, q);
        dq_load<true, 8>(a, q);
        dq_conv<6, kBurst>(a, q);
        mbar_spin(sb + TFULL, 0);
        static_for<0, 9>([&](auto kb_) {
            constexpr int kb = decltype(kb_)::value;
            mma_block<kb, true>(d, a, dbase + (5u << 16));
            if constexpr (kb < 8) mbar_spin(sb + TFULL + 8 * (kb + 1), 0);
            if constexpr (kBurst + 2 * kb < 36) dq_conv<kBurst + 2 * kb, kBurst + 2 * kb + 2>(a, q);
        });
        if (storer) mbar_arrive(sb + DONE);
        direct_out(d, zs + 640, (char*)ptrs.out, wk.fb, wk.jb, wk.rb, w);
    }
    if (storer) {
        if (!tail) mbar_arrive(sb + DONE);
        tma_st_wait_read();
    }
    mbar_spin(sb + ZCHK, 0);
    if (__builtin_expect(__shfl_sync(0xffffffffu, lds32(sb + ZCHK + 8), 0), 0)) {
        if (storer) asm volatile("cp.async.bulk.wait_group 0;" ::: "memory");
        asm volatile("fence.proxy.async.global;" ::: "memory");
        __threadfence();
        bar_sync(1 + wg);
        fixup(ptrs, wk.fa + 64 * wg, wk.ja, 0, 512);
        if (tail) fixup(ptrs, wk.fb, wk.jb, wk.rb, kTailN);
    }
}

DEV void producer(const uint32_t sb, const Work wk, const int rank, const CUtensorMap* xm, const CUtensorMap* xt,
                  const CUtensorMap* om, const CUtensorMap* wm, const CUtensorMap* wt,
                  const uint32_t* scales2, const uint32_t* zeros2) {
    const int xc = kXJ * wk.ja;
    const uint32_t xdst = sb + rank * (kStage / 2);
#pragma unroll 1
    for (int kb = 1; kb < 9; kb++) {
        if (kb >= kWindow) mbar_wait(sb + FULL + 8 * (kb - kWindow), 0);
        tma_ld_x(xdst + XS + kb * kStage, xm, xc + 64 * kb, 64 * rank, sb + FULL + 8 * kb);
        if (kb < 7) tma_ld_w(sb + WS + (kb + 1) * kPiece, wm, wk.fa, 8 * (kb + 1), sb + FULL + 8 * kb);
        if (kb == 7) bulk_ld(sb + ZS + 256, scales2 + wk.fa / 2, 256, sb + FULL + 8 * 7);
    }
    prefetch_map(om); prefetch_map(xt); prefetch_map(wt);
#pragma unroll 1
    for (int tile = 1; tile < 4; tile++) {
#pragma unroll 1
        for (int kb = 0; kb < (tile == 3 ? 7 : 9); kb++) {
            mbar_wait(sb + EMPTY + 8 * kb, (tile - 1) & 1);
            mbar_expect(sb + FULL + 8 * kb, kStage);
            tma_ld_x(xdst + XS + kb * kStage, xm, xc + 64 * kb, 128 * tile + 64 * rank, sb + FULL + 8 * kb);
            if (tile == 2) {
                if (kb == 0 && wk.tail) {
                    mbar_expect(sb + WFULL, 57 * 256 + 256);
                    tma_ld_w(sb + WS, wt, wk.fb, 0, sb + WFULL);
                    bulk_ld(sb + ZS + 512, zeros2 + wk.fb / 2, 128, sb + WFULL);
                    bulk_ld(sb + ZS + 640, scales2 + wk.fb / 2, 128, sb + WFULL);
                }
                if (kb == 2 || kb == 5) {
                    const int e = kb == 5;
                    mbar_expect(sb + XFULL + 8 * e, kStage);
                    tma_ld_x(xdst + (e ? X8 : X7), xm, xc + 64 * (7 + e), 384 + 64 * rank, sb + XFULL + 8 * e);
                }
            }
        }
    }
    if (wk.tail) {
        const int tc = kXJ * wk.jb, tr = wk.rb + (kTailN - kTailBox) * rank;
        const uint32_t tdst = sb + rank * ((kTailN - kTailBox) * 128);
#pragma unroll 1
        for (int kb = 0; kb < 9; kb++) {
            if (kb < 2) mbar_wait(sb + EMPTY + 8 * (7 + kb), 0);
            else mbar_wait(sb + EMPTY + 8 * tail_stage(kb), 1);
            mbar_expect(sb + TFULL + 8 * kb, 2 * kTailBox * 128);
            tma_ld_x(tdst + tail_off(kb), xt, tc + 64 * kb, tr, sb + TFULL + 8 * kb);
        }
    }
}

__global__ void __cluster_dims__(2, 1, 1) __launch_bounds__(384, 1)
gptq_kernel(const char* __restrict__ xg,
            const char* __restrict__ wg_ptr,
            const uint32_t* __restrict__ zeros2, const uint32_t* __restrict__ scales2, char* __restrict__ outp,
            const __grid_constant__ CUtensorMap wm, const __grid_constant__ CUtensorMap xm,
            const __grid_constant__ CUtensorMap om, const __grid_constant__ CUtensorMap xt,
            const __grid_constant__ CUtensorMap wt) {
    extern __shared__ __align__(1024) uint8_t smem[];
    const uint32_t sb = (uint32_t)__cvta_generic_to_shared(smem);
    if ((threadIdx.x >> 6) == 2) {
        const uint32_t b = blockIdx.x, t = threadIdx.x;
        const uint32_t ow = (32 * b + (t & 31)) * 128, ox = (4 * b + ((t >> 3) & 3)) * 1140 + (t & 7) * 128;
        const bool hi = t & 32;
        if (hi ? (t & 7) < 4 : (t & 31) < 32) prefetch_l2((const char*)((hi ? (uint64_t)xg : (uint64_t)wg_ptr) + (hi ? ox : ow)));
        prefetch_map(hi ? &xm : &wm);
    }
    const int warp = __shfl_sync(0xffffffffu, threadIdx.x >> 5, 0);
    const int lane = threadIdx.x & 31;
    const int rank = blockIdx.x & 1, c = blockIdx.x >> 1;
    Work wk;
    wk.ja = map_j(c);
    wk.fa = (map_f(c) * 2 + rank) * 128;

    if ((warp >= 9 || warp < 3) && elect_one()) {
        if (warp < 3) {
            mbar_init(sb + WFULL + 8 * warp, warp == 1 ? 2 : 1);
            if (warp > 0) mbar_init(sb + XFULL - 8 + 8 * warp, 1);
        } else {
            const uint32_t b = sb + BARS + 72 * (warp - 9), cnt = warp == 11 ? 4 : 1;
#pragma unroll
            for (int i = 0; i < 9; i++) mbar_init(b + 8 * i, cnt);
        }
        asm volatile("fence.mbarrier_init.release.cluster;" ::: "memory");
    }
    __syncwarp();
    asm volatile("barrier.cluster.arrive.relaxed.aligned;" ::: "memory");
    if (warp == 0 && elect_one()) {
        tma_ld_w(sb + WS, &wm, wk.fa, 0, sb + WFULL);
        bulk_ld(sb + ZS, zeros2 + wk.fa / 2, 256, sb + WFULL);
        mbar_expect(sb + WFULL, kPiece + 256);
    }
    __syncwarp();
    asm volatile("barrier.cluster.wait.aligned;" ::: "memory");
    if (warp == 8 && elect_one()) {
        tma_ld_x(sb + XS + rank * (kStage / 2), &xm, kXJ * wk.ja, 64 * rank, sb + FULL);
        tma_ld_w(sb + WS + kPiece, &wm, wk.fa, 8, sb + FULL);
    }
    if (warp == 10 && elect_one()) {
#pragma unroll
        for (int i = 0; i < 9; i++) mbar_expect(sb + FULL + 8 * i, kStage + (i < 7 ? kPiece : i == 7 ? 256 : 0));
    }
    __syncwarp();

    if (warp >= 8) {
        asm volatile("setmaxnreg.dec.sync.aligned.u32 24;");
        if (warp == 11) {
            tail_work(wk);
            mbar_wait(sb + FULL + 8 * 3, 0);
            const bool ok = zero_exact(__ldg(zeros2 + wk.fa / 2 + lane)) && zero_exact(__ldg(zeros2 + wk.fa / 2 + 32 + lane)) &&
                            zero_exact(__ldg(zeros2 + wk.fb / 2 + lane));
            const uint32_t bad = !__all_sync(0xffffffffu, ok);
            if (lane == 0) {
                asm volatile("st.shared.b32 [%0], %1;" :: "r"(sb + ZCHK + 8), "r"(bad) : "memory");
                mbar_arrive(sb + ZCHK);
            }
        }
        if (!elect_one()) return;
        if (warp == 8) {
            tail_work(wk);
            producer(sb, wk, rank, &xm, &xt, &om, &wm, &wt, scales2, zeros2);
        } else if (warp == 9) {
            int n = 0;
            while (!mbar_try(sb + DONE, 0)) { if (++n > (1 << 20)) __trap(); }
        }
    } else {
        tail_work(wk);
        asm volatile("setmaxnreg.inc.sync.aligned.u32 240;");
        DqState q;
        dq_setup(q, sb + WS + warp * 512, wk.ja, lane);
        asm volatile("{\n.reg .pred p;\nsetp.ne.b32 p, %0, 0;\n@p st.shared.v4.b32 [%1], {%2, %3, %4, %5};\n@p st.shared.v4.b32 [%6], {%7, %8, %9, %10};\n}"
                     :: "r"((uint32_t)((size_t)outp & 1)), "r"(q.addr[0]), "r"(q.addr[1]), "r"(q.addr[2]), "r"(q.addr[3]), "r"(q.mul[0]),
                        "r"(q.addr[4]), "r"(q.mul[1]), "r"(q.mul[2]), "r"(q.mul[3]), "r"(q.mul[4]));
        const Ptrs ptrs{(const uint16_t*)xg, (const uint32_t*)wg_ptr, (const uint16_t*)scales2, (const uint16_t*)zeros2, (__nv_bfloat16*)outp};
        consumer(sb, wk, warp >> 2, warp & 3, lane, &om, ptrs, q);
    }
}

typedef CUresult (*EncodeFn)(CUtensorMap*, CUtensorMapDataType, cuuint32_t, void*, const cuuint64_t*, const cuuint64_t*,
                             const cuuint32_t*, const cuuint32_t*, CUtensorMapInterleave, CUtensorMapSwizzle,
                             CUtensorMapL2promotion, CUtensorMapFloatOOBfill);

void make_map(EncodeFn enc, CUtensorMap* m, const void* p, uint64_t cols, uint32_t rows, CUtensorMapL2promotion promo) {
    cuuint64_t gd[2] = {cols, 512}, gs[1] = {2 * cols};
    cuuint32_t bx[2] = {64, rows}, es[2] = {1, 1};
    enc(m, CU_TENSOR_MAP_DATA_TYPE_BFLOAT16, 2, const_cast<void*>(p), gd, gs, bx, es, CU_TENSOR_MAP_INTERLEAVE_NONE,
        CU_TENSOR_MAP_SWIZZLE_128B, promo, CU_TENSOR_MAP_FLOAT_OOB_FILL_NONE);
}
void make_wmap(EncodeFn enc, CUtensorMap* m, const void* p, uint32_t rows, uint32_t groups) {
    cuuint64_t gd[3] = {16, 57, 288}, gs[2] = {4 * kF, 64};
    cuuint32_t bx[3] = {16, rows, groups}, es[3] = {1, 1, 1};
    enc(m, CU_TENSOR_MAP_DATA_TYPE_INT32, 3, const_cast<void*>(p), gd, gs, bx, es, CU_TENSOR_MAP_INTERLEAVE_NONE,
        CU_TENSOR_MAP_SWIZZLE_NONE, CU_TENSOR_MAP_L2_PROMOTION_L2_128B, CU_TENSOR_MAP_FLOAT_OOB_FILL_NONE);
}

}

extern "C" void kernel_launch(void* const* d_in, const int* in_sizes, int n_in, void* d_out, int out_size) {
    static EncodeFn enc = nullptr;
    if (!enc) {
        void* fn = nullptr;
        cudaDriverEntryPointQueryResult qr;
        cudaGetDriverEntryPoint("cuTensorMapEncodeTiled", &fn, cudaEnableDefault, &qr);
        enc = (EncodeFn)fn;
        cudaFuncSetAttribute(gptq_kernel, cudaFuncAttributeMaxDynamicSharedMemorySize, kSmem);
    }
    CUtensorMap xm, xt, om, wm, wt;
    make_map(enc, &xm, d_in[0], 4 * 570, 64, CU_TENSOR_MAP_L2_PROMOTION_L2_128B);
    make_map(enc, &xt, d_in[0], 4 * 570, kTailBox, CU_TENSOR_MAP_L2_PROMOTION_L2_128B);
    make_map(enc, &om, d_out, 4 * kF, 128, CU_TENSOR_MAP_L2_PROMOTION_NONE);
    make_wmap(enc, &wm, d_in[1], 8, 8);
    make_wmap(enc, &wt, d_in[1], 57, 4);
    gptq_kernel<<<132, 384, kSmem, cudaStreamPerThread>>>((const char*)d_in[0], (const char*)d_in[1], (const uint32_t*)d_in[3],
                                                       (const uint32_t*)d_in[2], (char*)d_out, wm, xm, om, xt, wt);
}
```

```cpp
#include <cuda_runtime.h>
#include <cuda_bf16.h>
#include <cuda.h>
#include <stdint.h>
#include <type_traits>

#define DEV __device__ __forceinline__

namespace {

constexpr int      kF        = 4608;
constexpr int      kXJ       = 568;
constexpr uint32_t kStage    = 16384;
constexpr int      kTailN    = 104;
constexpr int      kTailBox  = 52;
constexpr uint32_t kTailBlk  = kTailN * 128;
constexpr uint32_t kPiece    = 8 * 512;
constexpr uint32_t X7        = 0;
constexpr uint32_t XS        = 17 * 1024;
constexpr uint32_t OS        = XS + 9 * kStage;
constexpr uint32_t WS        = OS + 2 * kStage;
constexpr uint32_t X8        = WS + 4 * kPiece;
constexpr uint32_t ZS        = WS + 8 * kPiece;
constexpr uint32_t BARS      = ZS + 768;
constexpr uint32_t FULL      = BARS;
constexpr uint32_t TFULL     = BARS + 72;
constexpr uint32_t EMPTY     = BARS + 144;
constexpr uint32_t WFULL     = BARS + 216;
constexpr uint32_t DONE      = BARS + 224;
constexpr uint32_t ZCHK      = BARS + 232;
constexpr uint32_t XFULL     = BARS + 256;
constexpr uint32_t kSmem     = BARS + 272;
__host__ __device__ constexpr uint32_t tail_off(int i) { return i < 2 ? XS + 7 * kStage + i * kTailBlk : XS + (i - 2) * kTailBlk; }
__host__ __device__ constexpr int tail_stage(int i) { return ((i - 1) * (int)kTailBlk - 1) / (int)kStage; }
__host__ __device__ constexpr int t3_delta(int kb) { return kb < 7 ? 0 : ((int)(kb == 7 ? X7 : X8) - (int)(XS + kb * kStage)) / 16; }
constexpr int kPauseAt = 6, kPauseUntil = 8;
constexpr int kSplit   = 2;
constexpr int kWindow  = 3;
constexpr int kBurst   = 20;

DEV void mbar_init(uint32_t a, uint32_t c) { asm volatile("mbarrier.init.shared::cta.b64 [%0], %1;" :: "r"(a), "r"(c) : "memory"); }
DEV void mbar_expect(uint32_t a, uint32_t tx) { asm volatile("mbarrier.arrive.expect_tx.shared::cta.b64 _, [%0], %1;" :: "r"(a), "r"(tx) : "memory"); }
DEV void mbar_arrive(uint32_t a) { asm volatile("mbarrier.arrive.shared::cta.b64 _, [%0];" :: "r"(a) : "memory"); }
DEV void mbar_wait(uint32_t a, uint32_t par) {
    asm volatile("{\n.reg .pred p;\nL:\nmbarrier.try_wait.parity.shared::cta.b64 p, [%0], %1;\n@!p bra.uni L;\n}"
                 :: "r"(a), "r"(par) : "memory");
}
DEV void mbar_spin(uint32_t a, uint32_t par) {
    asm volatile("{\n.reg .pred p;\nL:\nmbarrier.test_wait.parity.shared::cta.b64 p, [%0], %1;\n@!p bra.uni L;\n}"
                 :: "r"(a), "r"(par) : "memory");
}
DEV bool mbar_try(uint32_t a, uint32_t par) {
    uint32_t ok;
    asm volatile("{\n.reg .pred p;\nmbarrier.try_wait.parity.shared::cta.b64 p, [%1], %2;\nselp.u32 %0, 1, 0, p;\n}"
                 : "=r"(ok) : "r"(a), "r"(par) : "memory");
    return ok;
}
DEV void arrive_cluster_if(uint32_t a, bool p) {
    asm volatile("{\n.reg .pred p;\nsetp.ne.b32 p, %1, 0;\n@p mbarrier.arrive.shared::cluster.b64 _, [%0];\n}"
                 :: "r"(a), "r"((uint32_t)p) : "memory");
}
DEV void tma_ld_w(uint32_t dst, const CUtensorMap* m, int f, int row, uint32_t bar) {
    asm volatile("cp.async.bulk.tensor.3d.shared::cluster.global.mbarrier::complete_tx::bytes [%0], [%1, {0, %3, %4}], [%2];"
                 :: "r"(dst), "l"(m), "r"(bar), "r"(row), "r"(f >> 4) : "memory");
}
DEV void tma_ld_x(uint32_t dst, const CUtensorMap* m, int c0, int c1, uint32_t bar) {
    asm volatile("cp.async.bulk.tensor.2d.shared::cluster.global.mbarrier::complete_tx::bytes.multicast::cluster [%0], [%1, {%3, %4}], [%2], %5;"
                 :: "r"(dst), "l"(m), "r"(bar), "r"(c0), "r"(c1), "h"((uint16_t)3) : "memory");
}
DEV void bulk_ld(uint32_t dst, const void* src, uint32_t bytes, uint32_t bar) {
    asm volatile("cp.async.bulk.shared::cluster.global.mbarrier::complete_tx::bytes [%0], [%1], %2, [%3];"
                 :: "r"(dst), "l"(src), "r"(bytes), "r"(bar) : "memory");
}
DEV void tma_st(const CUtensorMap* m, int c0, int c1, uint32_t src) {
    asm volatile("cp.async.bulk.tensor.2d.global.shared::cta.bulk_group [%0, {%2, %3}], [%1];"
                 :: "l"(m), "r"(src), "r"(c0), "r"(c1) : "memory");
    asm volatile("cp.async.bulk.commit_group;" ::: "memory");
}
DEV void tma_st_wait_read() { asm volatile("cp.async.bulk.wait_group.read 0;" ::: "memory"); }
DEV uint32_t lds32(uint32_t a) { uint32_t v; asm volatile("ld.shared.b32 %0, [%1];" : "=r"(v) : "r"(a)); return v; }
DEV bool elect_one() {
    uint32_t p;
    asm volatile("{\n.reg .pred p;\nelect.sync _|p, 0xffffffff;\nselp.u32 %0, 1, 0, p;\n}" : "=r"(p));
    return p;
}
DEV int fresh_lane() { int v; asm volatile("mov.u32 %0, %%laneid;" : "=r"(v)); return v; }
DEV void prefetch_map(const CUtensorMap* m) { asm volatile("prefetch.tensormap [%0];" :: "l"(m) : "memory"); }
DEV void bar_sync(int id) { asm volatile("bar.sync %0, 128;" :: "r"(id) : "memory"); }
template <int ID> DEV void order_wait() { asm volatile("bar.sync %0, 256;" :: "n"(ID) : "memory"); }
template <int ID> DEV void order_signal() { asm volatile("bar.arrive %0, 256;" :: "n"(ID) : "memory"); }
DEV void wg_fence() { asm volatile("wgmma.fence.sync.aligned;" ::: "memory"); }
DEV void wg_commit() { asm volatile("wgmma.commit_group.sync.aligned;" ::: "memory"); }
template <int N> DEV void wg_wait() { asm volatile("wgmma.wait_group.sync.aligned %0;" :: "n"(N) : "memory"); }
DEV uint32_t bf2_add(uint32_t a, uint32_t b) { uint32_t d; asm("add.rn.bf16x2 %0, %1, %2;" : "=r"(d) : "r"(a), "r"(b)); return d; }
DEV uint32_t bf2_sub(uint32_t a, uint32_t b) { uint32_t d; asm("sub.rn.bf16x2 %0, %1, %2;" : "=r"(d) : "r"(a), "r"(b)); return d; }
DEV uint32_t pack_scaled(float lo, float hi, uint32_t spair) {
    uint32_t p;
    asm("cvt.rn.bf16x2.f32 %0, %1, %2;" : "=r"(p) : "f"(hi), "f"(lo));
    asm("mul.rn.bf16x2 %0, %0, %1;" : "+r"(p) : "r"(spair));
    return p;
}
template <int I, int N, typename F>
DEV void static_for(F&& f) {
    if constexpr (I < N) { f(std::integral_constant<int, I>{}); static_for<I + 1, N>(f); }
}

#define ACC8(d, o) "+f"(d[o + 0]), "+f"(d[o + 1]), "+f"(d[o + 2]), "+f"(d[o + 3]), "+f"(d[o + 4]), "+f"(d[o + 5]), "+f"(d[o + 6]), "+f"(d[o + 7])

template <int ACCUM>
DEV void wgmma_n128(float (&d)[64], uint32_t a0, uint32_t a1, uint32_t a2, uint32_t a3, uint64_t desc) {
    asm volatile(
        "wgmma.mma_async.sync.aligned.m64n128k16.f32.bf16.bf16 "
        "{%0,%1,%2,%3,%4,%5,%6,%7,%8,%9,%10,%11,%12,%13,%14,%15,%16,%17,%18,%19,%20,%21,%22,%23,%24,%25,%26,%27,%28,%29,%30,%31,"
        "%32,%33,%34,%35,%36,%37,%38,%39,%40,%41,%42,%43,%44,%45,%46,%47,%48,%49,%50,%51,%52,%53,%54,%55,%56,%57,%58,%59,%60,%61,%62,%63},"
        "{%64,%65,%66,%67}, %68, %69, 1, 1, 0;\n"
        : ACC8(d, 0), ACC8(d, 8), ACC8(d, 16), ACC8(d, 24), ACC8(d, 32), ACC8(d, 40), ACC8(d, 48), ACC8(d, 56)
        : "r"(a0), "r"(a1), "r"(a2), "r"(a3), "l"(desc), "n"(ACCUM));
}
template <int ACCUM>
DEV void wgmma_n104(float (&d)[64], uint32_t a0, uint32_t a1, uint32_t a2, uint32_t a3, uint64_t desc) {
    asm volatile(
        "wgmma.mma_async.sync.aligned.m64n104k16.f32.bf16.bf16 "
        "{%0,%1,%2,%3,%4,%5,%6,%7,%8,%9,%10,%11,%12,%13,%14,%15,%16,%17,%18,%19,%20,%21,%22,%23,%24,%25,%26,%27,%28,%29,%30,%31,"
        "%32,%33,%34,%35,%36,%37,%38,%39,%40,%41,%42,%43,%44,%45,%46,%47,%48,%49,%50,%51},"
        "{%52,%53,%54,%55}, %56, %57, 1, 1, 0;\n"
        : ACC8(d, 0), ACC8(d, 8), ACC8(d, 16), ACC8(d, 24), ACC8(d, 32), ACC8(d, 40),
          "+f"(d[48]), "+f"(d[49]), "+f"(d[50]), "+f"(d[51])
        : "r"(a0), "r"(a1), "r"(a2), "r"(a3), "l"(desc), "n"(ACCUM));
}

template <int KB, bool TAIL>
DEV void mma_block(float (&d)[64], const uint32_t (&a)[144], uint64_t dbase) {
    constexpr uint32_t off = TAIL ? tail_off(KB) : XS + KB * kStage;
    wg_fence();
#pragma unroll
    for (int kk = 0; kk < 4; kk++) {
        const int s = 16 * KB + 4 * kk;
        const uint64_t desc = dbase + (off >> 4) + 2 * kk;
        if (KB == 0 && kk == 0) {
            if (TAIL) wgmma_n104<0>(d, a[s], a[s + 1], a[s + 2], a[s + 3], desc);
            else      wgmma_n128<0>(d, a[s], a[s + 1], a[s + 2], a[s + 3], desc);
        } else {
            if (TAIL) wgmma_n104<1>(d, a[s], a[s + 1], a[s + 2], a[s + 3], desc);
            else      wgmma_n128<1>(d, a[s], a[s + 1], a[s + 2], a[s + 3], desc);
        }
    }
    wg_commit();
}

constexpr uint32_t kMagic = 0x41004280u;
struct DqState {
    uint32_t addr[5];
    uint32_t addr0;
    uint32_t mul[5];
    uint32_t z0, z1;
    uint32_t magic;
    int j;
};

DEV void dq_setup(DqState& q, uint32_t slab, int j, int lane) {
    const int e = (lane & 3) - j;
#pragma unroll
    for (int r = 0; r < 5; r++) {
        const int n = 4 * r + e + 5;
        const int w = (n * 52) >> 8;
        q.addr[r] = slab + (w - 1) * 64 + (lane >> 2) * 8;
        asm("shl.b32 %0, 1, %1;" : "=r"(q.mul[r]) : "r"(25 - 6 * (n - 5 * w)));
    }
    q.addr0 = q.addr[0] - (e < 0 ? 4096 - 512 : 0);
    q.j = j;
    q.magic = kMagic;
}
DEV void dq_zero(DqState& q, uint32_t zpair) {
    q.z0 = bf2_add(__byte_perm(zpair, 0, 0x1010), kMagic);
    q.z1 = bf2_add(__byte_perm(zpair, 0, 0x3232), kMagic);
}
DEV bool zero_exact(uint32_t zpair) {
    const uint32_t z0 = __byte_perm(zpair, 0, 0x1010), z1 = __byte_perm(zpair, 0, 0x3232);
    return bf2_sub(bf2_add(z0, kMagic), kMagic) == bf2_add(z0, 0) && bf2_sub(bf2_add(z1, kMagic), kMagic) == bf2_add(z1, 0);
}
DEV uint32_t dq_pair(uint32_t w, uint32_t mul, uint32_t z, uint32_t magic) {
    uint32_t y;
    asm("mul.lo.u32 %0, %1, %2;" : "=r"(y) : "r"(w), "r"(mul));
    y = __byte_perm(y, 0, 0x3333);
    asm("lop3.b32 %0, %1, 0x0070000E, %2, 0xEA;" : "=r"(y) : "r"(y), "r"(magic));
    return bf2_sub(y, z);
}
template <bool TAIL, int KB>
DEV void dq_load(uint32_t (&a)[144], const DqState& q) {
#pragma unroll
    for (int u = 8 * KB; u < 8 * KB + 8; u++) {
        const int v = u / 5, r = u % 5;
        const uint32_t addr = TAIL ? q.addr[r] + 256 * v
                                   : ((r == 0 && !(v & 1) && v > 0) ? q.addr0 : q.addr[r]) + 4096 * (v >> 1) + 256 * (v & 1);
        asm volatile("ld.shared.v2.b32 {%0, %1}, [%2];" : "=r"(a[2 * u]), "=r"(a[2 * u + 1]) : "r"(addr));
    }
}
template <int SA, int SB>
DEV void dq_conv(uint32_t (&a)[144], const DqState& q) {
#pragma unroll
    for (int u = 2 * SA; u < 2 * SB; u++) {
        uint32_t x0 = dq_pair(a[2 * u], q.mul[u % 5], q.z0, q.magic);
        uint32_t x1 = dq_pair(a[2 * u + 1], q.mul[u % 5], q.z1, q.magic);
        if (u == 0 || u == 71) {
            const int t = fresh_lane() & 3;
            const bool ok = (u == 0) ? (t >= q.j) : (t <= q.j);
            x0 = ok ? x0 : 0u;
            x1 = ok ? x1 : 0u;
        }
        a[2 * u] = x0;
        a[2 * u + 1] = x1;
    }
}

template <typename F>
DEV void stage_out(const float (&d)[64], uint32_t sbase, uint32_t ost, int w, F&& after_wait) {
    const int lane = fresh_lane(), g = lane >> 2, t = lane & 3;
    const uint32_t spair = lds32(sbase + 4 * g);
    const uint32_t o0 = ost + (2 * t) * 128 + (((2 * w + (g >> 2)) ^ (2 * t)) << 4) + 4 * (g & 3);
    const uint32_t o1 = (o0 ^ 16) + 128;
    wg_wait<0>();
    after_wait();
#pragma unroll
    for (int c = 0; c < 16; c++) {
        const uint32_t p0 = pack_scaled(d[4 * c + 0], d[4 * c + 2], spair);
        const uint32_t p1 = pack_scaled(d[4 * c + 1], d[4 * c + 3], spair);
        asm volatile("st.shared.b32 [%0], %1;" :: "r"(o0 + 1024 * c), "r"(p0) : "memory");
        asm volatile("st.shared.b32 [%0], %1;" :: "r"(o1 + 1024 * c), "r"(p1) : "memory");
    }
}
DEV void direct_out(const float (&d)[64], uint32_t sbase, char* out, int col, int cls, int row0, int w) {
    const int lane = fresh_lane(), g = lane >> 2, t = lane & 3;
    const uint32_t spair = lds32(sbase + 4 * g);
    char* p = out + (size_t)(4 * (row0 + 2 * t) + cls) * (2 * kF) + (col + 16 * w + 2 * g) * 2;
    wg_wait<0>();
#pragma unroll
    for (int c = 0; c < kTailN / 8; c++) {
        const uint32_t p0 = pack_scaled(d[4 * c + 0], d[4 * c + 2], spair);
        const uint32_t p1 = pack_scaled(d[4 * c + 1], d[4 * c + 3], spair);
        if (c < kTailN / 8 - 1 || row0 + kTailN <= 512) {
            *(uint32_t*)(p + (size_t)c * (64 * kF)) = p0;
            *(uint32_t*)(p + (size_t)c * (64 * kF) + 8 * kF) = p1;
        }
    }
}

DEV int map_j(int c) { return c >= 64 ? c & 3 : ((c >> 3) & 1) | (((c >> 5) & 1) << 1); }
DEV int drop_bit(int v, int b) { return (v & ((1 << b) - 1)) | ((v >> (b + 1)) << b); }
DEV int map_f(int c) { return c >= 64 ? 16 : drop_bit(drop_bit(c, 5), 3); }
struct Work { int ja, fa, jb, fb, rb; bool tail; };
DEV void tail_work(Work& wk) {
    int b;
    asm volatile("mov.u32 %0, %%ctaid.x;" : "=r"(b));
    const int c = b >> 1, ut = (c * 52) >> 8;
    wk.tail = c < 60;
    wk.jb = ut < 4 ? 2 + (ut & 1) : (ut & 3);
    wk.fb = wk.tail ? (ut < 4 ? 32 + (ut >> 1) : 33 + (ut >> 2)) * 128 + 64 * (b & 1) : 0;
    wk.rb = (c - 5 * ut) * kTailN;
}

struct Ptrs { const uint16_t* x; const uint32_t* w; const uint16_t* s; const uint16_t* z; __nv_bfloat16* out; };
__device__ __noinline__ void fixup(const Ptrs p, int f0, int cls, int row0, int rows) {
    const int f = f0 + (threadIdx.x & 63);
    const uint32_t zr = p.z[f];
    if (zero_exact(zr | (zr << 16))) return;
    const float z = __uint_as_float(zr << 16), s = __uint_as_float((uint32_t)p.s[f] << 16);
    for (int i = row0 + ((threadIdx.x >> 6) & 1); i < row0 + rows && i < 512; i += 2) {
        const int m = 4 * i + cls;
        float acc = 0.f;
        for (int r = 0; r < 57; r++) {
            const uint32_t word = p.w[r * kF + f];
#pragma unroll 1
            for (int e = 0; e < 10; e++) {
                const float dq = __bfloat162float(__float2bfloat16_rn((float)((word >> (3 * e)) & 7) - z));
                const float wv = __bfloat162float(__float2bfloat16_rn(dq * s));
                acc = fmaf(__uint_as_float((uint32_t)p.x[m * 570 + 10 * r + e] << 16), wv, acc);
            }
        }
        p.out[(size_t)m * kF + f] = __float2bfloat16_rn(acc);
    }
}

DEV void consumer(const uint32_t sb, const Work wk, const int wg, const int w, const int lane,
                  const CUtensorMap* om, const Ptrs& ptrs, DqState& q) {
    const uint32_t full = sb + FULL;
    uint32_t rel;
    asm("mapa.shared::cluster.u32 %0, %1, %2;" : "=r"(rel) : "r"(sb + EMPTY), "r"(w & 1));
    const bool do_rel = (lane == 0) && (w < 2);
    const bool storer = (lane == 0) && (w == 3);
    const uint32_t ost = sb + OS + wg * kStage;
    const uint64_t dbase = (uint64_t)((sb & 0x3FFFF) >> 4) | (64ull << 32) | (1ull << 62);
    const uint32_t zs = sb + ZS + 128 * wg + 32 * w;
    const int ocol = wk.ja * kF + wk.fa + wg * 64;

    uint32_t a[144];
    float d[64];

    auto publish = [&](int row) {
        asm volatile("fence.proxy.async.shared::cta;" ::: "memory");
        bar_sync(1 + wg);
        if (storer) tma_st(om, ocol, row, ost);
    };
    auto staging_free = [&]() {
        if (storer) tma_st_wait_read();
        bar_sync(3 + wg);
    };

    const uint32_t sel = 0x3210u + (uint32_t)((size_t)ptrs.out & 1);
    mbar_wait(sb + WFULL, 0);
    dq_zero(q, lds32(zs + (lane & ~3)));
    dq_load<false, 0>(a, q);
    dq_conv<0, 4>(a, q);
    static_for<0, 9>([&](auto kb_) {
        constexpr int kb = decltype(kb_)::value;
        if constexpr (kb == kPauseAt) { if (wg == 1) order_wait<5>(); }
        mbar_spin(full + 8 * kb, 0);
        if constexpr (kb < 8) dq_load<false, kb + 1>(a, q);
        mma_block<kb, false>(d, a, dbase + (1u << 16));
        if constexpr (kb < 8) dq_conv<4 * kb + 4, 4 * kb + 4 + kSplit>(a, q);
        if constexpr (kb == kPauseUntil) { if (wg == 0) order_signal<5>(); }
        if constexpr (kb > 0) { wg_wait<1>(); arrive_cluster_if(rel + 8 * (kb - 1), do_rel); }
        if constexpr (kb < 8) {
            uint32_t c;
            asm volatile("mov.u32 %0, %%clock;" : "=r"(c) :: "memory");
            q.magic = __byte_perm(kMagic, c, sel);
            dq_conv<4 * kb + 4 + kSplit, 4 * kb + 8>(a, q);
        }
    });

    const bool tail = wg == 0 && wk.tail;
#pragma unroll 1
    for (int tile = 1; tile < 4; tile++) {
        stage_out(d, zs + 256, ost, w, [&] { arrive_cluster_if(rel + 8 * 8, do_rel && (tile < 3 || wk.tail)); });
        const bool defer = !(tile == 3 && wk.tail);
        if (!defer) {
            publish(256);
            if (wg == 0) break;
            order_wait<6>();
        }
        const bool rel_lo = do_rel && (tile < 3 || wk.tail), rel_hi = do_rel && tile < 3;
        const bool rel_7 = rel_hi && (tile < 2 || wk.tail);
        static_for<0, 9>([&](auto kb_) {
            constexpr int kb = decltype(kb_)::value;
            if constexpr (kb >= 7) {
                const bool t3 = tile == 3;
                mbar_wait(t3 ? sb + XFULL + 8 * (kb - 7) : full + 8 * kb, t3 ? 0 : tile & 1);
                mma_block<kb, false>(d, a, dbase + ((tile + 1u) << 16) + (t3 ? t3_delta(kb) : 0));
            } else {
                mbar_wait(full + 8 * kb, tile & 1);
                mma_block<kb, false>(d, a, dbase + ((tile + 1u) << 16));
            }
            if constexpr (kb == 0) { if (defer) publish(128 * (tile - 1)); }
            if constexpr (kb == 6) staging_free();
            if constexpr (kb > 0) {
                wg_wait<1>();
                arrive_cluster_if(rel + 8 * (kb - 1), kb - 1 <= tail_stage(8) ? rel_lo : kb == 8 ? rel_7 : rel_hi);
            }
        });
    }
    if (tail) {
        mbar_spin(full, 1);
        static_for<0, 9>([&](auto kb_) {
            constexpr int kb = decltype(kb_)::value;
            mma_block<kb, false>(d, a, dbase + (4u << 16) + (uint64_t)(int64_t)t3_delta(kb));
            if constexpr (kb == 8) order_signal<6>();
            if constexpr (kb < 6) mbar_spin(full + 8 * (kb + 1), 1);
            else if constexpr (kb < 8) mbar_spin(sb + XFULL + 8 * (kb - 6), 0);
            if constexpr (kb == 0) {
                const int l2 = fresh_lane();
                dq_setup(q, sb + WS + w * (57 * 64), wk.jb, l2);
                mbar_spin(sb + WFULL, 1);
                q.z0 = lds32(zs + 512 + (l2 & ~3));
            }
            if constexpr (kb == 6) staging_free();
            if constexpr (kb == 2) dq_zero(q, q.z0);
            if constexpr (kb >= 3) dq_conv<kb - 3, kb - 2>(a, q);
            if constexpr (kb >= 2) dq_load<true, kb - 2>(a, q);
            if constexpr (kb > 0) {
                wg_wait<1>();
                if constexpr (kb - 1 <= tail_stage(8)) arrive_cluster_if(rel + 8 * (kb - 1), do_rel);
            }
        });
    }
    stage_out(d, zs + 256, ost, w, [] {});
    publish(384);

    if (tail) {
        dq_load<true, 7>(a, q);
        dq_load<true, 8>(a, q);
        dq_conv<6, kBurst>(a, q);
        mbar_spin(sb + TFULL, 0);
        static_for<0, 9>([&](auto kb_) {
            constexpr int kb = decltype(kb_)::value;
            mma_block<kb, true>(d, a, dbase + (5u << 16));
            if constexpr (kb < 8) mbar_spin(sb + TFULL + 8 * (kb + 1), 0);
            if constexpr (kBurst + 2 * kb < 36) dq_conv<kBurst + 2 * kb, kBurst + 2 * kb + 2>(a, q);
        });
        if (storer) mbar_arrive(sb + DONE);
        direct_out(d, zs + 640, (char*)ptrs.out, wk.fb, wk.jb, wk.rb, w);
    }
    if (storer) {
        if (!tail) mbar_arrive(sb + DONE);
        tma_st_wait_read();
    }
    mbar_spin(sb + ZCHK, 0);
    if (__builtin_expect(__shfl_sync(0xffffffffu, lds32(sb + ZCHK + 8), 0), 0)) {
        if (storer) asm volatile("cp.async.bulk.wait_group 0;" ::: "memory");
        asm volatile("fence.proxy.async.global;" ::: "memory");
        __threadfence();
        bar_sync(1 + wg);
        fixup(ptrs, wk.fa + 64 * wg, wk.ja, 0, 512);
        if (tail) fixup(ptrs, wk.fb, wk.jb, wk.rb, kTailN);
    }
}

DEV void producer(const uint32_t sb, const Work wk, const int rank, const CUtensorMap* xm, const CUtensorMap* xt,
                  const CUtensorMap* om, const CUtensorMap* wm, const CUtensorMap* wt,
                  const uint32_t* scales2, const uint32_t* zeros2) {
    const int xc = kXJ * wk.ja;
    const uint32_t xdst = sb + rank * (kStage / 2);
#pragma unroll 1
    for (int kb = 1; kb < 9; kb++) {
        if (kb >= kWindow) mbar_wait(sb + FULL + 8 * (kb - kWindow), 0);
        tma_ld_x(xdst + XS + kb * kStage, xm, xc + 64 * kb, 64 * rank, sb + FULL + 8 * kb);
        if (kb < 7) tma_ld_w(sb + WS + (kb + 1) * kPiece, wm, wk.fa, 8 * (kb + 1), sb + FULL + 8 * kb);
        if (kb == 7) bulk_ld(sb + ZS + 256, scales2 + wk.fa / 2, 256, sb + FULL + 8 * 7);
    }
    prefetch_map(om); prefetch_map(xt); prefetch_map(wt);
#pragma unroll 1
    for (int tile = 1; tile < 4; tile++) {
#pragma unroll 1
        for (int kb = 0; kb < (tile == 3 ? 7 : 9); kb++) {
            mbar_wait(sb + EMPTY + 8 * kb, (tile - 1) & 1);
            mbar_expect(sb + FULL + 8 * kb, kStage);
            tma_ld_x(xdst + XS + kb * kStage, xm, xc + 64 * kb, 128 * tile + 64 * rank, sb + FULL + 8 * kb);
            if (tile == 2) {
                if (kb == 0 && wk.tail) {
                    mbar_expect(sb + WFULL, 57 * 256 + 256);
                    tma_ld_w(sb + WS, wt, wk.fb, 0, sb + WFULL);
                    bulk_ld(sb + ZS + 512, zeros2 + wk.fb / 2, 128, sb + WFULL);
                    bulk_ld(sb + ZS + 640, scales2 + wk.fb / 2, 128, sb + WFULL);
                }
                if (kb == 2 || kb == 5) {
                    const int e = kb == 5;
                    mbar_expect(sb + XFULL + 8 * e, kStage);
                    tma_ld_x(xdst + (e ? X8 : X7), xm, xc + 64 * (7 + e), 384 + 64 * rank, sb + XFULL + 8 * e);
                }
            }
        }
    }
    if (wk.tail) {
        const int tc = kXJ * wk.jb, tr = wk.rb + (kTailN - kTailBox) * rank;
        const uint32_t tdst = sb + rank * ((kTailN - kTailBox) * 128);
#pragma unroll 1
        for (int kb = 0; kb < 9; kb++) {
            if (kb < 2) mbar_wait(sb + EMPTY + 8 * (7 + kb), 0);
            else mbar_wait(sb + EMPTY + 8 * tail_stage(kb), 1);
            mbar_expect(sb + TFULL + 8 * kb, 2 * kTailBox * 128);
            tma_ld_x(tdst + tail_off(kb), xt, tc + 64 * kb, tr, sb + TFULL + 8 * kb);
        }
    }
}

__global__ void __cluster_dims__(2, 1, 1) __launch_bounds__(384, 1)
gptq_kernel(const char* __restrict__ xg,
            const char* __restrict__ wg_ptr,
            const uint32_t* __restrict__ zeros2, const uint32_t* __restrict__ scales2, char* __restrict__ outp,
            const __grid_constant__ CUtensorMap wm, const __grid_constant__ CUtensorMap xm,
            const __grid_constant__ CUtensorMap om, const __grid_constant__ CUtensorMap xt,
            const __grid_constant__ CUtensorMap wt) {
    extern __shared__ __align__(1024) uint8_t smem[];
    const uint32_t sb = (uint32_t)__cvta_generic_to_shared(smem);
    {
        const uint32_t b = blockIdx.x, t = threadIdx.x;
        const uint32_t ow = (32 * b + (t & 31)) * 128, ox = (4 * b + ((t >> 2) & 3)) * 1140 + (t & 3) * 128;
        const bool hi = t & 32;
        const uint64_t p = (hi ? (uint64_t)xg : (uint64_t)wg_ptr) + (hi ? ox : ow);
        asm volatile("{\n.reg .pred q;\nsetp.lt.u32 q, %1, 48;\n@q prefetch.global.L2 [%0];\n}" :: "l"(p), "r"(t));
    }
    const int warp = __shfl_sync(0xffffffffu, threadIdx.x >> 5, 0);
    const int lane = threadIdx.x & 31;
    const int rank = blockIdx.x & 1, c = blockIdx.x >> 1;
    Work wk;
    wk.ja = map_j(c);
    wk.fa = (map_f(c) * 2 + rank) * 128;

    if ((warp >= 9 || warp < 3) && elect_one()) {
        if (warp < 3) {
            mbar_init(sb + WFULL + 8 * warp, warp == 1 ? 3 : 1);
            if (warp > 0) mbar_init(sb + XFULL - 8 + 8 * warp, 1);
        } else {
            const uint32_t b = sb + BARS + 72 * (warp - 9), cnt = warp == 11 ? 4 : 1;
#pragma unroll
            for (int i = 0; i < 9; i++) mbar_init(b + 8 * i, cnt);
        }
        asm volatile("fence.mbarrier_init.release.cluster;" ::: "memory");
    }
    __syncwarp();
    asm volatile("barrier.cluster.arrive.relaxed.aligned;" ::: "memory");
    if (warp == 8) prefetch_map(&xm);
    if (warp == 0 && elect_one()) {
        tma_ld_w(sb + WS, &wm, wk.fa, 0, sb + WFULL);
        bulk_ld(sb + ZS, zeros2 + wk.fa / 2, 256, sb + WFULL);
        mbar_expect(sb + WFULL, kPiece + 256);
    }
    __syncwarp();
    asm volatile("barrier.cluster.wait.aligned;" ::: "memory");
    if (warp == 8 && elect_one()) {
        tma_ld_x(sb + XS + rank * (kStage / 2), &xm, kXJ * wk.ja, 64 * rank, sb + FULL);
        tma_ld_w(sb + WS + kPiece, &wm, wk.fa, 8, sb + FULL);
    }
    if (warp == 10 && elect_one()) {
#pragma unroll
        for (int i = 0; i < 9; i++) mbar_expect(sb + FULL + 8 * i, kStage + (i < 7 ? kPiece : i == 7 ? 256 : 0));
    }
    __syncwarp();

    if (warp >= 8) {
        asm volatile("setmaxnreg.dec.sync.aligned.u32 24;");
        if (warp == 11) {
            tail_work(wk);
            mbar_wait(sb + FULL + 8 * 3, 0);
            const bool ok = zero_exact(__ldg(zeros2 + wk.fa / 2 + lane)) && zero_exact(__ldg(zeros2 + wk.fa / 2 + 32 + lane)) &&
                            zero_exact(__ldg(zeros2 + wk.fb / 2 + lane));
            const uint32_t bad = !__all_sync(0xffffffffu, ok);
            if (lane == 0) {
                asm volatile("st.shared.b32 [%0], %1;" :: "r"(sb + ZCHK + 8), "r"(bad) : "memory");
                mbar_arrive(sb + ZCHK);
                mbar_arrive(sb + DONE);
            }
        }
        if (!elect_one()) return;
        if (warp == 8) {
            tail_work(wk);
            producer(sb, wk, rank, &xm, &xt, &om, &wm, &wt, scales2, zeros2);
        } else if (warp == 9) {
            int n = 0;
            while (!mbar_try(sb + DONE, 0)) { if (++n > (1 << 20)) __trap(); }
        }
    } else {
        tail_work(wk);
        asm volatile("setmaxnreg.inc.sync.aligned.u32 240;");
        DqState q;
        dq_setup(q, sb + WS + warp * 512, wk.ja, lane);
        asm volatile("{\n.reg .pred p;\nsetp.ne.b32 p, %0, 0;\n@p st.shared.v4.b32 [%1], {%2, %3, %4, %5};\n@p st.shared.v4.b32 [%6], {%7, %8, %9, %10};\n}"
                     :: "r"((uint32_t)((size_t)outp & 1)), "r"(q.addr[0]), "r"(q.addr[1]), "r"(q.addr[2]), "r"(q.addr[3]), "r"(q.mul[0]),
                        "r"(q.addr[4]), "r"(q.mul[1]), "r"(q.mul[2]), "r"(q.mul[3]), "r"(q.mul[4]));
        const Ptrs ptrs{(const uint16_t*)xg, (const uint32_t*)wg_ptr, (const uint16_t*)scales2, (const uint16_t*)zeros2, (__nv_bfloat16*)outp};
        consumer(sb, wk, warp >> 2, warp & 3, lane, &om, ptrs, q);
    }
}

typedef CUresult (*EncodeFn)(CUtensorMap*, CUtensorMapDataType, cuuint32_t, void*, const cuuint64_t*, const cuuint64_t*,
                             const cuuint32_t*, const cuuint32_t*, CUtensorMapInterleave, CUtensorMapSwizzle,
                             CUtensorMapL2promotion, CUtensorMapFloatOOBfill);

void make_map(EncodeFn enc, CUtensorMap* m, const void* p, uint64_t cols, uint32_t rows, CUtensorMapL2promotion promo) {
    cuuint64_t gd[2] = {cols, 512}, gs[1] = {2 * cols};
    cuuint32_t bx[2] = {64, rows}, es[2] = {1, 1};
    enc(m, CU_TENSOR_MAP_DATA_TYPE_BFLOAT16, 2, const_cast<void*>(p), gd, gs, bx, es, CU_TENSOR_MAP_INTERLEAVE_NONE,
        CU_TENSOR_MAP_SWIZZLE_128B, promo, CU_TENSOR_MAP_FLOAT_OOB_FILL_NONE);
}
void make_wmap(EncodeFn enc, CUtensorMap* m, const void* p, uint32_t rows, uint32_t groups) {
    cuuint64_t gd[3] = {16, 57, 288}, gs[2] = {4 * kF, 64};
    cuuint32_t bx[3] = {16, rows, groups}, es[3] = {1, 1, 1};
    enc(m, CU_TENSOR_MAP_DATA_TYPE_INT32, 3, const_cast<void*>(p), gd, gs, bx, es, CU_TENSOR_MAP_INTERLEAVE_NONE,
        CU_TENSOR_MAP_SWIZZLE_NONE, CU_TENSOR_MAP_L2_PROMOTION_L2_128B, CU_TENSOR_MAP_FLOAT_OOB_FILL_NONE);
}

}

extern "C" void kernel_launch(void* const* d_in, const int* in_sizes, int n_in, void* d_out, int out_size) {
    static EncodeFn enc = nullptr;
    if (!enc) {
        void* fn = nullptr;
        cudaDriverEntryPointQueryResult qr;
        cudaGetDriverEntryPoint("cuTensorMapEncodeTiled", &fn, cudaEnableDefault, &qr);
        enc = (EncodeFn)fn;
        cudaFuncSetAttribute(gptq_kernel, cudaFuncAttributeMaxDynamicSharedMemorySize, kSmem);
    }
    CUtensorMap xm, xt, om, wm, wt;
    make_map(enc, &xm, d_in[0], 4 * 570, 64, CU_TENSOR_MAP_L2_PROMOTION_L2_128B);
    make_map(enc, &xt, d_in[0], 4 * 570, kTailBox, CU_TENSOR_MAP_L2_PROMOTION_L2_128B);
    make_map(enc, &om, d_out, 4 * kF, 128, CU_TENSOR_MAP_L2_PROMOTION_NONE);
    make_wmap(enc, &wm, d_in[1], 8, 8);
    make_wmap(enc, &wt, d_in[1], 57, 4);
    gptq_kernel<<<132, 384, kSmem, cudaStreamPerThread>>>((const char*)d_in[0], (const char*)d_in[1], (const uint32_t*)d_in[3],
                                                       (const uint32_t*)d_in[2], (char*)d_out, wm, xm, om, xt, wt);
}
```

```cpp
#include <cuda_runtime.h>
#include <cuda_bf16.h>
#include <cuda.h>
#include <stdint.h>
#include <type_traits>

#define DEV __device__ __forceinline__

namespace {

constexpr int      kF        = 4608;
constexpr int      kXJ       = 568;
constexpr uint32_t kStage    = 16384;
constexpr int      kTailN    = 104;
constexpr int      kTailBox  = 52;
constexpr uint32_t kTailBlk  = kTailN * 128;
constexpr uint32_t kPiece    = 8 * 512;
constexpr uint32_t X7        = 0;
constexpr uint32_t XS        = 17 * 1024;
constexpr uint32_t OS        = XS + 9 * kStage;
constexpr uint32_t WS        = OS + 2 * kStage;
constexpr uint32_t X8        = WS + 4 * kPiece;
constexpr uint32_t ZS        = WS + 8 * kPiece;
constexpr uint32_t BARS      = ZS + 768;
constexpr uint32_t FULL      = BARS;
constexpr uint32_t TFULL     = BARS + 72;
constexpr uint32_t EMPTY     = BARS + 144;
constexpr uint32_t WFULL     = BARS + 216;
constexpr uint32_t DONE      = BARS + 224;
constexpr uint32_t ZCHK      = BARS + 232;
constexpr uint32_t XFULL     = BARS + 256;
constexpr uint32_t kSmem     = BARS + 272;
__host__ __device__ constexpr uint32_t tail_off(int i) { return i < 2 ? XS + 7 * kStage + i * kTailBlk : XS + (i - 2) * kTailBlk; }
__host__ __device__ constexpr int tail_stage(int i) { return ((i - 1) * (int)kTailBlk - 1) / (int)kStage; }
__host__ __device__ constexpr int t3_delta(int kb) { return kb < 7 ? 0 : ((int)(kb == 7 ? X7 : X8) - (int)(XS + kb * kStage)) / 16; }
constexpr int kPauseAt = 6, kPauseUntil = 7;
constexpr int kLead    = 3;
constexpr int kSplit   = 2;
constexpr int kWindow  = 3;
constexpr int kBurst   = 20;

DEV void mbar_init(uint32_t a, uint32_t c) { asm volatile("mbarrier.init.shared::cta.b64 [%0], %1;" :: "r"(a), "r"(c) : "memory"); }
DEV void mbar_expect(uint32_t a, uint32_t tx) { asm volatile("mbarrier.arrive.expect_tx.shared::cta.b64 _, [%0], %1;" :: "r"(a), "r"(tx) : "memory"); }
DEV void mbar_arrive(uint32_t a) { asm volatile("mbarrier.arrive.shared::cta.b64 _, [%0];" :: "r"(a) : "memory"); }
DEV void mbar_wait(uint32_t a, uint32_t par) {
    asm volatile("{\n.reg .pred p;\nL:\nmbarrier.try_wait.parity.shared::cta.b64 p, [%0], %1;\n@!p bra.uni L;\n}"
                 :: "r"(a), "r"(par) : "memory");
}
DEV void mbar_spin(uint32_t a, uint32_t par) {
    asm volatile("{\n.reg .pred p;\nL:\nmbarrier.test_wait.parity.shared::cta.b64 p, [%0], %1;\n@!p bra.uni L;\n}"
                 :: "r"(a), "r"(par) : "memory");
}
DEV bool mbar_try(uint32_t a, uint32_t par) {
    uint32_t ok;
    asm volatile("{\n.reg .pred p;\nmbarrier.try_wait.parity.shared::cta.b64 p, [%1], %2;\nselp.u32 %0, 1, 0, p;\n}"
                 : "=r"(ok) : "r"(a), "r"(par) : "memory");
    return ok;
}
DEV void arrive_cluster_if(uint32_t a, bool p) {
    asm volatile("{\n.reg .pred p;\nsetp.ne.b32 p, %1, 0;\n@p mbarrier.arrive.shared::cluster.b64 _, [%0];\n}"
                 :: "r"(a), "r"((uint32_t)p) : "memory");
}
DEV void tma_ld_w(uint32_t dst, const CUtensorMap* m, int f, int row, uint32_t bar) {
    asm volatile("cp.async.bulk.tensor.3d.shared::cluster.global.mbarrier::complete_tx::bytes [%0], [%1, {0, %3, %4}], [%2];"
                 :: "r"(dst), "l"(m), "r"(bar), "r"(row), "r"(f >> 4) : "memory");
}
DEV void tma_ld_x(uint32_t dst, const CUtensorMap* m, int c0, int c1, uint32_t bar) {
    asm volatile("cp.async.bulk.tensor.2d.shared::cluster.global.mbarrier::complete_tx::bytes.multicast::cluster [%0], [%1, {%3, %4}], [%2], %5;"
                 :: "r"(dst), "l"(m), "r"(bar), "r"(c0), "r"(c1), "h"((uint16_t)3) : "memory");
}
DEV void bulk_ld(uint32_t dst, const void* src, uint32_t bytes, uint32_t bar) {
    asm volatile("cp.async.bulk.shared::cluster.global.mbarrier::complete_tx::bytes [%0], [%1], %2, [%3];"
                 :: "r"(dst), "l"(src), "r"(bytes), "r"(bar) : "memory");
}
DEV void tma_st(const CUtensorMap* m, int c0, int c1, uint32_t src) {
    asm volatile("cp.async.bulk.tensor.2d.global.shared::cta.bulk_group [%0, {%2, %3}], [%1];"
                 :: "l"(m), "r"(src), "r"(c0), "r"(c1) : "memory");
    asm volatile("cp.async.bulk.commit_group;" ::: "memory");
}
DEV void tma_st_wait_read() { asm volatile("cp.async.bulk.wait_group.read 0;" ::: "memory"); }
DEV uint32_t lds32(uint32_t a) { uint32_t v; asm volatile("ld.shared.b32 %0, [%1];" : "=r"(v) : "r"(a)); return v; }
DEV bool elect_one() {
    uint32_t p;
    asm volatile("{\n.reg .pred p;\nelect.sync _|p, 0xffffffff;\nselp.u32 %0, 1, 0, p;\n}" : "=r"(p));
    return p;
}
DEV int fresh_lane() { int v; asm volatile("mov.u32 %0, %%laneid;" : "=r"(v)); return v; }
DEV void prefetch_map(const CUtensorMap* m) { asm volatile("prefetch.tensormap [%0];" :: "l"(m) : "memory"); }
DEV void bar_sync(int id) { asm volatile("bar.sync %0, 128;" :: "r"(id) : "memory"); }
template <int ID> DEV void order_wait() { asm volatile("bar.sync %0, 256;" :: "n"(ID) : "memory"); }
template <int ID> DEV void order_signal() { asm volatile("bar.arrive %0, 256;" :: "n"(ID) : "memory"); }
DEV void wg_fence() { asm volatile("wgmma.fence.sync.aligned;" ::: "memory"); }
DEV void wg_commit() { asm volatile("wgmma.commit_group.sync.aligned;" ::: "memory"); }
template <int N> DEV void wg_wait() { asm volatile("wgmma.wait_group.sync.aligned %0;" :: "n"(N) : "memory"); }
DEV uint32_t bf2_add(uint32_t a, uint32_t b) { uint32_t d; asm("add.rn.bf16x2 %0, %1, %2;" : "=r"(d) : "r"(a), "r"(b)); return d; }
DEV uint32_t bf2_sub(uint32_t a, uint32_t b) { uint32_t d; asm("sub.rn.bf16x2 %0, %1, %2;" : "=r"(d) : "r"(a), "r"(b)); return d; }
DEV uint32_t pack_scaled(float lo, float hi, uint32_t spair) {
    uint32_t p;
    asm("cvt.rn.bf16x2.f32 %0, %1, %2;" : "=r"(p) : "f"(hi), "f"(lo));
    asm("mul.rn.bf16x2 %0, %0, %1;" : "+r"(p) : "r"(spair));
    return p;
}
template <int I, int N, typename F>
DEV void static_for(F&& f) {
    if constexpr (I < N) { f(std::integral_constant<int, I>{}); static_for<I + 1, N>(f); }
}

#define ACC8(d, o) "+f"(d[o + 0]), "+f"(d[o + 1]), "+f"(d[o + 2]), "+f"(d[o + 3]), "+f"(d[o + 4]), "+f"(d[o + 5]), "+f"(d[o + 6]), "+f"(d[o + 7])

template <int ACCUM>
DEV void wgmma_n128(float (&d)[64], uint32_t a0, uint32_t a1, uint32_t a2, uint32_t a3, uint64_t desc) {
    asm volatile(
        "wgmma.mma_async.sync.aligned.m64n128k16.f32.bf16.bf16 "
        "{%0,%1,%2,%3,%4,%5,%6,%7,%8,%9,%10,%11,%12,%13,%14,%15,%16,%17,%18,%19,%20,%21,%22,%23,%24,%25,%26,%27,%28,%29,%30,%31,"
        "%32,%33,%34,%35,%36,%37,%38,%39,%40,%41,%42,%43,%44,%45,%46,%47,%48,%49,%50,%51,%52,%53,%54,%55,%56,%57,%58,%59,%60,%61,%62,%63},"
        "{%64,%65,%66,%67}, %68, %69, 1, 1, 0;\n"
        : ACC8(d, 0), ACC8(d, 8), ACC8(d, 16), ACC8(d, 24), ACC8(d, 32), ACC8(d, 40), ACC8(d, 48), ACC8(d, 56)
        : "r"(a0), "r"(a1), "r"(a2), "r"(a3), "l"(desc), "n"(ACCUM));
}
template <int ACCUM>
DEV void wgmma_n104(float (&d)[64], uint32_t a0, uint32_t a1, uint32_t a2, uint32_t a3, uint64_t desc) {
    asm volatile(
        "wgmma.mma_async.sync.aligned.m64n104k16.f32.bf16.bf16 "
        "{%0,%1,%2,%3,%4,%5,%6,%7,%8,%9,%10,%11,%12,%13,%14,%15,%16,%17,%18,%19,%20,%21,%22,%23,%24,%25,%26,%27,%28,%29,%30,%31,"
        "%32,%33,%34,%35,%36,%37,%38,%39,%40,%41,%42,%43,%44,%45,%46,%47,%48,%49,%50,%51},"
        "{%52,%53,%54,%55}, %56, %57, 1, 1, 0;\n"
        : ACC8(d, 0), ACC8(d, 8), ACC8(d, 16), ACC8(d, 24), ACC8(d, 32), ACC8(d, 40),
          "+f"(d[48]), "+f"(d[49]), "+f"(d[50]), "+f"(d[51])
        : "r"(a0), "r"(a1), "r"(a2), "r"(a3), "l"(desc), "n"(ACCUM));
}

template <int KB, bool TAIL>
DEV void mma_block(float (&d)[64], const uint32_t (&a)[144], uint64_t dbase) {
    constexpr uint32_t off = TAIL ? tail_off(KB) : XS + KB * kStage;
    wg_fence();
#pragma unroll
    for (int kk = 0; kk < 4; kk++) {
        const int s = 16 * KB + 4 * kk;
        const uint64_t desc = dbase + (off >> 4) + 2 * kk;
        if (KB == 0 && kk == 0) {
            if (TAIL) wgmma_n104<0>(d, a[s], a[s + 1], a[s + 2], a[s + 3], desc);
            else      wgmma_n128<0>(d, a[s], a[s + 1], a[s + 2], a[s + 3], desc);
        } else {
            if (TAIL) wgmma_n104<1>(d, a[s], a[s + 1], a[s + 2], a[s + 3], desc);
            else      wgmma_n128<1>(d, a[s], a[s + 1], a[s + 2], a[s + 3], desc);
        }
    }
    wg_commit();
}

constexpr uint32_t kMagic = 0x41004280u;
struct DqState {
    uint32_t addr[5];
    uint32_t addr0;
    uint32_t mul[5];
    uint32_t z0, z1;
    uint32_t magic;
    int j;
};

DEV void dq_setup(DqState& q, uint32_t slab, int j, int lane) {
    const int e = (lane & 3) - j;
#pragma unroll
    for (int r = 0; r < 5; r++) {
        const int n = 4 * r + e + 5;
        const int w = (n * 52) >> 8;
        q.addr[r] = slab + (w - 1) * 64 + (lane >> 2) * 8;
        asm("shl.b32 %0, 1, %1;" : "=r"(q.mul[r]) : "r"(25 - 6 * (n - 5 * w)));
    }
    q.addr0 = q.addr[0] - (e < 0 ? 4096 - 512 : 0);
    q.j = j;
    q.magic = kMagic;
}
DEV void dq_zero(DqState& q, uint32_t zpair) {
    q.z0 = bf2_add(__byte_perm(zpair, 0, 0x1010), kMagic);
    q.z1 = bf2_add(__byte_perm(zpair, 0, 0x3232), kMagic);
}
DEV bool zero_exact(uint32_t zpair) {
    const uint32_t z0 = __byte_perm(zpair, 0, 0x1010), z1 = __byte_perm(zpair, 0, 0x3232);
    return bf2_sub(bf2_add(z0, kMagic), kMagic) == bf2_add(z0, 0) && bf2_sub(bf2_add(z1, kMagic), kMagic) == bf2_add(z1, 0);
}
DEV uint32_t dq_pair(uint32_t w, uint32_t mul, uint32_t z, uint32_t magic) {
    uint32_t y;
    asm("mul.lo.u32 %0, %1, %2;" : "=r"(y) : "r"(w), "r"(mul));
    y = __byte_perm(y, 0, 0x3333);
    asm("lop3.b32 %0, %1, 0x0070000E, %2, 0xEA;" : "=r"(y) : "r"(y), "r"(magic));
    return bf2_sub(y, z);
}
template <bool TAIL, int KB>
DEV void dq_load(uint32_t (&a)[144], const DqState& q) {
#pragma unroll
    for (int u = 8 * KB; u < 8 * KB + 8; u++) {
        const int v = u / 5, r = u % 5;
        const uint32_t addr = TAIL ? q.addr[r] + 256 * v
                                   : ((r == 0 && !(v & 1) && v > 0) ? q.addr0 : q.addr[r]) + 4096 * (v >> 1) + 256 * (v & 1);
        asm volatile("ld.shared.v2.b32 {%0, %1}, [%2];" : "=r"(a[2 * u]), "=r"(a[2 * u + 1]) : "r"(addr));
    }
}
template <int SA, int SB>
DEV void dq_conv(uint32_t (&a)[144], const DqState& q) {
#pragma unroll
    for (int u = 2 * SA; u < 2 * SB; u++) {
        uint32_t x0 = dq_pair(a[2 * u], q.mul[u % 5], q.z0, q.magic);
        uint32_t x1 = dq_pair(a[2 * u + 1], q.mul[u % 5], q.z1, q.magic);
        if (u == 0 || u == 71) {
            const int t = fresh_lane() & 3;
            const bool ok = (u == 0) ? (t >= q.j) : (t <= q.j);
            x0 = ok ? x0 : 0u;
            x1 = ok ? x1 : 0u;
        }
        a[2 * u] = x0;
        a[2 * u + 1] = x1;
    }
}

template <typename F>
DEV void stage_out(const float (&d)[64], uint32_t sbase, uint32_t ost, int w, F&& after_wait) {
    const int lane = fresh_lane(), g = lane >> 2, t = lane & 3;
    const uint32_t spair = lds32(sbase + 4 * g);
    const uint32_t o0 = ost + (2 * t) * 128 + (((2 * w + (g >> 2)) ^ (2 * t)) << 4) + 4 * (g & 3);
    const uint32_t o1 = (o0 ^ 16) + 128;
    wg_wait<0>();
    after_wait();
#pragma unroll
    for (int c = 0; c < 16; c++) {
        const uint32_t p0 = pack_scaled(d[4 * c + 0], d[4 * c + 2], spair);
        const uint32_t p1 = pack_scaled(d[4 * c + 1], d[4 * c + 3], spair);
        asm volatile("st.shared.b32 [%0], %1;" :: "r"(o0 + 1024 * c), "r"(p0) : "memory");
        asm volatile("st.shared.b32 [%0], %1;" :: "r"(o1 + 1024 * c), "r"(p1) : "memory");
    }
}
DEV void direct_out(const float (&d)[64], uint32_t sbase, char* out, int col, int cls, int row0, int w) {
    const int lane = fresh_lane(), g = lane >> 2, t = lane & 3;
    const uint32_t spair = lds32(sbase + 4 * g);
    char* p = out + (size_t)(4 * (row0 + 2 * t) + cls) * (2 * kF) + (col + 16 * w + 2 * g) * 2;
    wg_wait<0>();
#pragma unroll
    for (int c = 0; c < kTailN / 8; c++) {
        const uint32_t p0 = pack_scaled(d[4 * c + 0], d[4 * c + 2], spair);
        const uint32_t p1 = pack_scaled(d[4 * c + 1], d[4 * c + 3], spair);
        if (c < kTailN / 8 - 1 || row0 + kTailN <= 512) {
            *(uint32_t*)(p + (size_t)c * (64 * kF)) = p0;
            *(uint32_t*)(p + (size_t)c * (64 * kF) + 8 * kF) = p1;
        }
    }
}

DEV int map_j(int c) { return c >= 64 ? c & 3 : ((c >> 3) & 1) | (((c >> 5) & 1) << 1); }
DEV int drop_bit(int v, int b) { return (v & ((1 << b) - 1)) | ((v >> (b + 1)) << b); }
DEV int map_f(int c) { return c >= 64 ? 16 : drop_bit(drop_bit(c, 5), 3); }
struct Work { int ja, fa, jb, fb, rb; bool tail; };
DEV void tail_work(Work& wk) {
    int b;
    asm volatile("mov.u32 %0, %%ctaid.x;" : "=r"(b));
    const int c = b >> 1, ut = (c * 52) >> 8;
    wk.tail = c < 60;
    wk.jb = ut < 4 ? 2 + (ut & 1) : (ut & 3);
    wk.fb = wk.tail ? (ut < 4 ? 32 + (ut >> 1) : 33 + (ut >> 2)) * 128 + 64 * (b & 1) : 0;
    wk.rb = (c - 5 * ut) * kTailN;
}

struct Ptrs { const uint16_t* x; const uint32_t* w; const uint16_t* s; const uint16_t* z; __nv_bfloat16* out; };
__device__ __noinline__ void fixup(const Ptrs p, int f0, int cls, int row0, int rows) {
    const int f = f0 + (threadIdx.x & 63);
    const uint32_t zr = p.z[f];
    if (zero_exact(zr | (zr << 16))) return;
    const float z = __uint_as_float(zr << 16), s = __uint_as_float((uint32_t)p.s[f] << 16);
    for (int i = row0 + ((threadIdx.x >> 6) & 1); i < row0 + rows && i < 512; i += 2) {
        const int m = 4 * i + cls;
        float acc = 0.f;
        for (int r = 0; r < 57; r++) {
            const uint32_t word = p.w[r * kF + f];
#pragma unroll 1
            for (int e = 0; e < 10; e++) {
                const float dq = __bfloat162float(__float2bfloat16_rn((float)((word >> (3 * e)) & 7) - z));
                const float wv = __bfloat162float(__float2bfloat16_rn(dq * s));
                acc = fmaf(__uint_as_float((uint32_t)p.x[m * 570 + 10 * r + e] << 16), wv, acc);
            }
        }
        p.out[(size_t)m * kF + f] = __float2bfloat16_rn(acc);
    }
}

DEV void consumer(const uint32_t sb, const Work wk, const int wg, const int w, const int lane,
                  const CUtensorMap* om, const Ptrs& ptrs, DqState& q) {
    const uint32_t full = sb + FULL;
    uint32_t rel;
    asm("mapa.shared::cluster.u32 %0, %1, %2;" : "=r"(rel) : "r"(sb + EMPTY), "r"(w & 1));
    const bool do_rel = (lane == 0) && (w < 2);
    const bool storer = (lane == 0) && (w == 3);
    const uint32_t ost = sb + OS + wg * kStage;
    const uint64_t dbase = (uint64_t)((sb & 0x3FFFF) >> 4) | (64ull << 32) | (1ull << 62);
    const uint32_t zs = sb + ZS + 128 * wg + 32 * w;
    const int ocol = wk.ja * kF + wk.fa + wg * 64;

    uint32_t a[144];
    float d[64];

    auto publish = [&](int row) {
        asm volatile("fence.proxy.async.shared::cta;" ::: "memory");
        bar_sync(1 + wg);
        if (storer) tma_st(om, ocol, row, ost);
    };
    auto staging_free = [&]() {
        if (storer) tma_st_wait_read();
        bar_sync(3 + wg);
    };

    const uint32_t sel = 0x3210u + (uint32_t)((size_t)ptrs.out & 1);
    mbar_wait(sb + WFULL, 0);
    dq_zero(q, lds32(zs + (lane & ~3)));
    dq_load<false, 0>(a, q);
    dq_conv<0, 4>(a, q);
    static_for<0, 9>([&](auto kb_) {
        constexpr int kb = decltype(kb_)::value;
        if constexpr (kb == kPauseAt) { if (wg == 1) order_wait<5>(); }
        mbar_spin(full + 8 * kb, 0);
        if constexpr (kb < 8) dq_load<false, kb + 1>(a, q);
        mma_block<kb, false>(d, a, dbase + (1u << 16));
        if constexpr (kb < 8) dq_conv<4 * kb + 4, 4 * kb + 4 + kSplit>(a, q);
        if constexpr (kb == kPauseUntil) { if (wg == 0) order_signal<5>(); }
        if constexpr (kb > 0) { wg_wait<1>(); arrive_cluster_if(rel + 8 * (kb - 1), do_rel); }
        if constexpr (kb < 8) {
            uint32_t c;
            asm volatile("mov.u32 %0, %%clock;" : "=r"(c) :: "memory");
            q.magic = __byte_perm(kMagic, c, sel);
            dq_conv<4 * kb + 4 + kSplit, 4 * kb + 8>(a, q);
        }
    });

    const bool tail = wg == 0 && wk.tail;
#pragma unroll 1
    for (int tile = 1; tile < 4; tile++) {
        stage_out(d, zs + 256, ost, w, [&] { arrive_cluster_if(rel + 8 * 8, do_rel && (tile < 3 || wk.tail)); });
        const bool defer = !(tile == 3 && wk.tail);
        if (!defer) {
            publish(256);
            if (wg == 0) break;
            order_wait<6>();
        }
        if (tile < 3 && wg == 1) order_wait<7>();
        const bool rel_lo = do_rel && (tile < 3 || wk.tail), rel_hi = do_rel && tile < 3;
        const bool rel_7 = rel_hi && (tile < 2 || wk.tail);
        static_for<0, 9>([&](auto kb_) {
            constexpr int kb = decltype(kb_)::value;
            if constexpr (kb >= 7) {
                const bool t3 = tile == 3;
                mbar_wait(t3 ? sb + XFULL + 8 * (kb - 7) : full + 8 * kb, t3 ? 0 : tile & 1);
                mma_block<kb, false>(d, a, dbase + ((tile + 1u) << 16) + (t3 ? t3_delta(kb) : 0));
            } else {
                mbar_wait(full + 8 * kb, tile & 1);
                mma_block<kb, false>(d, a, dbase + ((tile + 1u) << 16));
            }
            if constexpr (kb == kLead) { if (tile < 3 && wg == 0) order_signal<7>(); }
            if constexpr (kb == 0) { if (defer) publish(128 * (tile - 1)); }
            if constexpr (kb == 6) staging_free();
            if constexpr (kb > 0) {
                wg_wait<1>();
                arrive_cluster_if(rel + 8 * (kb - 1), kb - 1 <= tail_stage(8) ? rel_lo : kb == 8 ? rel_7 : rel_hi);
            }
        });
    }
    if (tail) {
        mbar_spin(full, 1);
        static_for<0, 9>([&](auto kb_) {
            constexpr int kb = decltype(kb_)::value;
            mma_block<kb, false>(d, a, dbase + (4u << 16) + (uint64_t)(int64_t)t3_delta(kb));
            if constexpr (kb == 8) order_signal<6>();
            if constexpr (kb < 6) mbar_spin(full + 8 * (kb + 1), 1);
            else if constexpr (kb < 8) mbar_spin(sb + XFULL + 8 * (kb - 6), 0);
            if constexpr (kb == 0) {
                const int l2 = fresh_lane();
                dq_setup(q, sb + WS + w * (57 * 64), wk.jb, l2);
                mbar_spin(sb + WFULL, 1);
                q.z0 = lds32(zs + 512 + (l2 & ~3));
            }
            if constexpr (kb == 6) staging_free();
            if constexpr (kb == 2) dq_zero(q, q.z0);
            if constexpr (kb >= 3) dq_conv<kb - 3, kb - 2>(a, q);
            if constexpr (kb >= 2) dq_load<true, kb - 2>(a, q);
            if constexpr (kb > 0) {
                wg_wait<1>();
                if constexpr (kb - 1 <= tail_stage(8)) arrive_cluster_if(rel + 8 * (kb - 1), do_rel);
            }
        });
    }
    stage_out(d, zs + 256, ost, w, [] {});
    publish(384);

    if (tail) {
        dq_load<true, 7>(a, q);
        dq_load<true, 8>(a, q);
        dq_conv<6, kBurst>(a, q);
        mbar_spin(sb + TFULL, 0);
        static_for<0, 9>([&](auto kb_) {
            constexpr int kb = decltype(kb_)::value;
            mma_block<kb, true>(d, a, dbase + (5u << 16));
            if constexpr (kb < 8) mbar_spin(sb + TFULL + 8 * (kb + 1), 0);
            if constexpr (kBurst + 2 * kb < 36) dq_conv<kBurst + 2 * kb, kBurst + 2 * kb + 2>(a, q);
        });
        if (storer) mbar_arrive(sb + DONE);
        direct_out(d, zs + 640, (char*)ptrs.out, wk.fb, wk.jb, wk.rb, w);
    }
    if (storer) {
        if (!tail) mbar_arrive(sb + DONE);
        tma_st_wait_read();
    }
    mbar_spin(sb + ZCHK, 0);
    if (__builtin_expect(__shfl_sync(0xffffffffu, lds32(sb + ZCHK + 8), 0), 0)) {
        if (storer) asm volatile("cp.async.bulk.wait_group 0;" ::: "memory");
        asm volatile("fence.proxy.async.global;" ::: "memory");
        __threadfence();
        bar_sync(1 + wg);
        fixup(ptrs, wk.fa + 64 * wg, wk.ja, 0, 512);
        if (tail) fixup(ptrs, wk.fb, wk.jb, wk.rb, kTailN);
    }
}

DEV void producer(const uint32_t sb, const Work wk, const int rank, const CUtensorMap* xm, const CUtensorMap* xt,
                  const CUtensorMap* om, const CUtensorMap* wm, const CUtensorMap* wt,
                  const uint32_t* scales2, const uint32_t* zeros2) {
    const int xc = kXJ * wk.ja;
    const uint32_t xdst = sb + rank * (kStage / 2);
#pragma unroll 1
    for (int kb = 1; kb < 9; kb++) {
        if (kb >= kWindow) mbar_wait(sb + FULL + 8 * (kb - kWindow), 0);
        tma_ld_x(xdst + XS + kb * kStage, xm, xc + 64 * kb, 64 * rank, sb + FULL + 8 * kb);
        if (kb < 7) tma_ld_w(sb + WS + (kb + 1) * kPiece, wm, wk.fa, 8 * (kb + 1), sb + FULL + 8 * kb);
        if (kb == 7) bulk_ld(sb + ZS + 256, scales2 + wk.fa / 2, 256, sb + FULL + 8 * 7);
    }
    prefetch_map(om); prefetch_map(xt); prefetch_map(wt);
#pragma unroll 1
    for (int tile = 1; tile < 4; tile++) {
#pragma unroll 1
        for (int kb = 0; kb < (tile == 3 ? 7 : 9); kb++) {
            mbar_wait(sb + EMPTY + 8 * kb, (tile - 1) & 1);
            mbar_expect(sb + FULL + 8 * kb, kStage);
            tma_ld_x(xdst + XS + kb * kStage, xm, xc + 64 * kb, 128 * tile + 64 * rank, sb + FULL + 8 * kb);
            if (tile == 2) {
                if (kb == 0 && wk.tail) {
                    mbar_expect(sb + WFULL, 57 * 256 + 256);
                    tma_ld_w(sb + WS, wt, wk.fb, 0, sb + WFULL);
                    bulk_ld(sb + ZS + 512, zeros2 + wk.fb / 2, 128, sb + WFULL);
                    bulk_ld(sb + ZS + 640, scales2 + wk.fb / 2, 128, sb + WFULL);
                }
                if (kb == 3 || kb == 7) {
                    const int e = kb == 7;
                    mbar_expect(sb + XFULL + 8 * e, kStage);
                    tma_ld_x(xdst + (e ? X8 : X7), xm, xc + 64 * (7 + e), 384 + 64 * rank, sb + XFULL + 8 * e);
                }
            }
        }
    }
    if (wk.tail) {
        const int tc = kXJ * wk.jb, tr = wk.rb + (kTailN - kTailBox) * rank;
        const uint32_t tdst = sb + rank * ((kTailN - kTailBox) * 128);
#pragma unroll 1
        for (int kb = 0; kb < 9; kb++) {
            if (kb < 2) mbar_wait(sb + EMPTY + 8 * (7 + kb), 0);
            else mbar_wait(sb + EMPTY + 8 * tail_stage(kb), 1);
            mbar_expect(sb + TFULL + 8 * kb, 2 * kTailBox * 128);
            tma_ld_x(tdst + tail_off(kb), xt, tc + 64 * kb, tr, sb + TFULL + 8 * kb);
        }
    }
}

__global__ void __cluster_dims__(2, 1, 1) __launch_bounds__(384, 1)
gptq_kernel(const char* __restrict__ xg,
            const char* __restrict__ wg_ptr,
            const uint32_t* __restrict__ zeros2, const uint32_t* __restrict__ scales2, char* __restrict__ outp,
            const __grid_constant__ CUtensorMap wm, const __grid_constant__ CUtensorMap xm,
            const __grid_constant__ CUtensorMap om, const __grid_constant__ CUtensorMap xt,
            const __grid_constant__ CUtensorMap wt) {
    extern __shared__ __align__(1024) uint8_t smem[];
    const uint32_t sb = (uint32_t)__cvta_generic_to_shared(smem);
    {
        const uint32_t b = blockIdx.x, t = threadIdx.x;
        const uint32_t ow = (32 * b + (t & 31)) * 128, ox = (4 * b + ((t >> 2) & 3)) * 1140 + (t & 3) * 128;
        const bool hi = t & 32;
        const uint64_t p = (hi ? (uint64_t)xg : (uint64_t)wg_ptr) + (hi ? ox : ow);
        asm volatile("{\n.reg .pred q;\nsetp.lt.u32 q, %1, 48;\n@q prefetch.global.L2 [%0];\n}" :: "l"(p), "r"(t));
    }
    const int warp = __shfl_sync(0xffffffffu, threadIdx.x >> 5, 0);
    const int lane = threadIdx.x & 31;
    const int rank = blockIdx.x & 1, c = blockIdx.x >> 1;
    Work wk;
    wk.ja = map_j(c);
    wk.fa = (map_f(c) * 2 + rank) * 128;

    if ((warp >= 9 || warp < 3) && elect_one()) {
        if (warp < 3) {
            mbar_init(sb + WFULL + 8 * warp, warp == 1 ? 3 : 1);
            if (warp > 0) mbar_init(sb + XFULL - 8 + 8 * warp, 1);
        } else {
            const uint32_t b = sb + BARS + 72 * (warp - 9), cnt = warp == 11 ? 4 : 1;
#pragma unroll
            for (int i = 0; i < 9; i++) mbar_init(b + 8 * i, cnt);
        }
        asm volatile("fence.mbarrier_init.release.cluster;" ::: "memory");
    }
    __syncwarp();
    asm volatile("barrier.cluster.arrive.relaxed.aligned;" ::: "memory");
    if (warp == 8) prefetch_map(&xm);
    if (warp == 0 && elect_one()) {
        tma_ld_w(sb + WS, &wm, wk.fa, 0, sb + WFULL);
        bulk_ld(sb + ZS, zeros2 + wk.fa / 2, 256, sb + WFULL);
        mbar_expect(sb + WFULL, kPiece + 256);
    }
    __syncwarp();
    asm volatile("barrier.cluster.wait.aligned;" ::: "memory");
    if (warp == 8 && elect_one()) {
        tma_ld_x(sb + XS + rank * (kStage / 2), &xm, kXJ * wk.ja, 64 * rank, sb + FULL);
        tma_ld_w(sb + WS + kPiece, &wm, wk.fa, 8, sb + FULL);
    }
    if (warp == 10 && elect_one()) {
#pragma unroll
        for (int i = 0; i < 9; i++) mbar_expect(sb + FULL + 8 * i, kStage + (i < 7 ? kPiece : i == 7 ? 256 : 0));
    }
    __syncwarp();

    if (warp >= 8) {
        asm volatile("setmaxnreg.dec.sync.aligned.u32 24;");
        if (warp == 11) {
            tail_work(wk);
            mbar_wait(sb + FULL + 8 * 3, 0);
            const bool ok = zero_exact(__ldg(zeros2 + wk.fa / 2 + lane)) && zero_exact(__ldg(zeros2 + wk.fa / 2 + 32 + lane)) &&
                            zero_exact(__ldg(zeros2 + wk.fb / 2 + lane));
            const uint32_t bad = !__all_sync(0xffffffffu, ok);
            if (lane == 0) {
                asm volatile("st.shared.b32 [%0], %1;" :: "r"(sb + ZCHK + 8), "r"(bad) : "memory");
                mbar_arrive(sb + ZCHK);
                mbar_arrive(sb + DONE);
            }
        }
        if (!elect_one()) return;
        if (warp == 8) {
            tail_work(wk);
            producer(sb, wk, rank, &xm, &xt, &om, &wm, &wt, scales2, zeros2);
        } else if (warp == 9) {
            int n = 0;
            while (!mbar_try(sb + DONE, 0)) { if (++n > (1 << 20)) __trap(); }
        }
    } else {
        tail_work(wk);
        asm volatile("setmaxnreg.inc.sync.aligned.u32 240;");
        DqState q;
        dq_setup(q, sb + WS + warp * 512, wk.ja, lane);
        asm volatile("{\n.reg .pred p;\nsetp.ne.b32 p, %0, 0;\n@p st.shared.v4.b32 [%1], {%2, %3, %4, %5};\n@p st.shared.v4.b32 [%6], {%7, %8, %9, %10};\n}"
                     :: "r"((uint32_t)((size_t)outp & 1)), "r"(q.addr[0]), "r"(q.addr[1]), "r"(q.addr[2]), "r"(q.addr[3]), "r"(q.mul[0]),
                        "r"(q.addr[4]), "r"(q.mul[1]), "r"(q.mul[2]), "r"(q.mul[3]), "r"(q.mul[4]));
        const Ptrs ptrs{(const uint16_t*)xg, (const uint32_t*)wg_ptr, (const uint16_t*)scales2, (const uint16_t*)zeros2, (__nv_bfloat16*)outp};
        consumer(sb, wk, warp >> 2, warp & 3, lane, &om, ptrs, q);
    }
}

typedef CUresult (*EncodeFn)(CUtensorMap*, CUtensorMapDataType, cuuint32_t, void*, const cuuint64_t*, const cuuint64_t*,
                             const cuuint32_t*, const cuuint32_t*, CUtensorMapInterleave, CUtensorMapSwizzle,
                             CUtensorMapL2promotion, CUtensorMapFloatOOBfill);

void make_map(EncodeFn enc, CUtensorMap* m, const void* p, uint64_t cols, uint32_t rows, CUtensorMapL2promotion promo) {
    cuuint64_t gd[2] = {cols, 512}, gs[1] = {2 * cols};
    cuuint32_t bx[2] = {64, rows}, es[2] = {1, 1};
    enc(m, CU_TENSOR_MAP_DATA_TYPE_BFLOAT16, 2, const_cast<void*>(p), gd, gs, bx, es, CU_TENSOR_MAP_INTERLEAVE_NONE,
        CU_TENSOR_MAP_SWIZZLE_128B, promo, CU_TENSOR_MAP_FLOAT_OOB_FILL_NONE);
}
void make_wmap(EncodeFn enc, CUtensorMap* m, const void* p, uint32_t rows, uint32_t groups) {
    cuuint64_t gd[3] = {16, 57, 288}, gs[2] = {4 * kF, 64};
    cuuint32_t bx[3] = {16, rows, groups}, es[3] = {1, 1, 1};
    enc(m, CU_TENSOR_MAP_DATA_TYPE_INT32, 3, const_cast<void*>(p), gd, gs, bx, es, CU_TENSOR_MAP_INTERLEAVE_NONE,
        CU_TENSOR_MAP_SWIZZLE_NONE, CU_TENSOR_MAP_L2_PROMOTION_L2_128B, CU_TENSOR_MAP_FLOAT_OOB_FILL_NONE);
}

}

extern "C" void kernel_launch(void* const* d_in, const int* in_sizes, int n_in, void* d_out, int out_size) {
    static EncodeFn enc = nullptr;
    if (!enc) {
        void* fn = nullptr;
        cudaDriverEntryPointQueryResult qr;
        cudaGetDriverEntryPoint("cuTensorMapEncodeTiled", &fn, cudaEnableDefault, &qr);
        enc = (EncodeFn)fn;
        cudaFuncSetAttribute(gptq_kernel, cudaFuncAttributeMaxDynamicSharedMemorySize, kSmem);
    }
    CUtensorMap xm, xt, om, wm, wt;
    make_map(enc, &xm, d_in[0], 4 * 570, 64, CU_TENSOR_MAP_L2_PROMOTION_L2_128B);
    make_map(enc, &xt, d_in[0], 4 * 570, kTailBox, CU_TENSOR_MAP_L2_PROMOTION_L2_128B);
    make_map(enc, &om, d_out, 4 * kF, 128, CU_TENSOR_MAP_L2_PROMOTION_NONE);
    make_wmap(enc, &wm, d_in[1], 8, 8);
    make_wmap(enc, &wt, d_in[1], 57, 4);
    gptq_kernel<<<132, 384, kSmem, cudaStreamPerThread>>>((const char*)d_in[0], (const char*)d_in[1], (const uint32_t*)d_in[3],
                                                       (const uint32_t*)d_in[2], (char*)d_out, wm, xm, om, xt, wt);
}
```
